```python
import torch

def _softmax(x, axis=-1):
    return torch.softmax(x, dim=axis)

def _gelu(x):
    return torch.nn.functional.gelu(x, approximate='tanh')

def _silu(x):
    return torch.nn.functional.silu(x)

def _sigmoid(x):
    return torch.sigmoid(x)

def _layernorm(x, axis=-1, eps=1e-05):
    m = x.mean(dim=axis, keepdim=True)
    v = x.var(dim=axis, keepdim=True, unbiased=False)
    return (x - m) / torch.sqrt(v + eps)

def _scatter_add(tgt, idx, src, axis=0):
    return tgt.clone().index_add_(axis, idx, src)

def _segment_sum(src, seg, n):
    out = torch.zeros((n,) + src.shape[1:], dtype=src.dtype)
    return out.index_add_(0, seg, src)

def _pad(x, pw):
    flat = tuple((v for pair in reversed(pw) for v in pair))
    return torch.nn.functional.pad(x, flat)
kernel_name = 'gated_mix__memory_aug_recurrent_mem_tr__dense_activation_squared_relu__prompt'

def setup_inputs():

    _w = lambda a: (lambda t: t.to(torch.bfloat16) if t.is_floating_point() else t)(torch.as_tensor(a))

    def _A_setup():
        B, S, Dm = (1, 2048, 1024)
        H, Dh = (32, 128)
        M, seg = (8, 32)
        seg = min(seg, S)
        S = S // seg * seg
        return {'x': _w((lambda *s: torch.randn(*s, dtype=torch.bfloat16) * 0.05)(B, S, Dm)), 'mem0': _w((lambda *s: torch.randn(*s, dtype=torch.bfloat16) * 0.8)(B, M, Dm)), 'Wq': _w((lambda *s: torch.randn(*s, dtype=torch.bfloat16) * 3.2)(Dm, H, Dh) * Dm ** (-0.5)), 'Wk': _w((lambda *s: torch.randn(*s, dtype=torch.bfloat16) * 3.2)(Dm, H, Dh) * Dm ** (-0.5)), 'Wv': _w((lambda *s: torch.randn(*s, dtype=torch.bfloat16) * 0.8)(Dm, H, Dh) * Dm ** (-0.5)), 'Wo': _w((lambda *s: torch.randn(*s, dtype=torch.bfloat16) * 0.8)(H, Dh, Dm) * (H * Dh) ** (-0.5)), 'seg_len': seg}
    _A_in = _A_setup()

    def _B_setup():
        B, S, D, F = (1, 2048, 1024, 3584)
        return {'x': _w((lambda *s: torch.randn(*s, dtype=torch.bfloat16) * 0.05)(B, S, D)), 'w1': _w((lambda *s: torch.randn(*s, dtype=torch.bfloat16) * 0.05)(D, F)), 'b1': _w((lambda *s: torch.randn(*s, dtype=torch.bfloat16) * 0.05)(F)), 'w2': _w((lambda *s: torch.randn(*s, dtype=torch.bfloat16) * 0.05)(F, D)), 'b2': _w((lambda *s: torch.randn(*s, dtype=torch.bfloat16) * 0.05)(D))}
    _B_in = _B_setup()
    return {'A_x': _A_in['x'], 'A_mem0': _A_in['mem0'], 'A_Wq': _A_in['Wq'], 'A_Wk': _A_in['Wk'], 'A_Wv': _A_in['Wv'], 'A_Wo': _A_in['Wo'], 'A_seg_len': _A_in['seg_len'], 'B_x': _B_in['x'], 'B_w1': _B_in['w1'], 'B_b1': _B_in['b1'], 'B_w2': _B_in['w2'], 'B_b2': _B_in['b2'], 'gate_w': _w((lambda *s: torch.randn(*s, dtype=torch.bfloat16) * 0.05)(1024) * 16.0)}

def reference(A_x, A_mem0, A_Wq, A_Wk, A_Wv, A_Wo, A_seg_len, B_x, B_w1, B_b1, B_w2, B_b2, gate_w):

    def _A_ref(x, mem0, Wq, Wk, Wv, Wo, seg_len):
        B, S, Dm = x.shape
        H, Dh = (Wq.shape[1], Wq.shape[2])
        M = mem0.shape[1]
        scale = Dh ** (-0.5)
        n_seg = S // seg_len
        L = M + seg_len
        idx = torch.arange(L)
        mask = (idx[:, None] < M) | (idx[:, None] >= idx[None, :])
        mem = mem0
        outs = []
        for s in range(n_seg):
            xs = x[:, s * seg_len:(s + 1) * seg_len, :].clone()
            h = torch.concatenate([mem, xs], axis=1)
            q = torch.einsum('btd,dhe->bhte', h, Wq)
            k = torch.einsum('btd,dhe->bhte', h, Wk)
            v = torch.einsum('btd,dhe->bhte', h, Wv)
            scores = torch.einsum('bhqe,bhke->bhqk', q, k) * scale
            scores = torch.where(mask[None, None], scores, -1000000000.0)
            p = _softmax(scores, axis=-1)
            o = torch.einsum('bhqk,bhke->bhqe', p, v)
            o = torch.einsum('bhte,hed->btd', o, Wo)
            mem = o[:, :M, :].clone()
            outs.append(o[:, M:, :])
        return torch.concatenate(outs, axis=1)

    def _B_ref(x, w1, b1, w2, b2):
        h = torch.einsum('bsd,df->bsf', x, w1) + b1
        zero = torch.zeros_like(h)
        r = torch.where(h > zero, h, zero)
        h = r * r
        out = torch.einsum('bsf,fd->bsd', h, w2) + b2
        return out
    x = A_x
    g = _sigmoid((x * gate_w).sum(-1, keepdims=True))
    a = _A_ref(x, A_mem0, A_Wq, A_Wk, A_Wv, A_Wo, A_seg_len)
    b = _B_ref(x, B_w1, B_b1, B_w2, B_b2)
    return g * a + (1 - g) * b
```

```cpp
#include <cuda_runtime.h>
#include <cuda_bf16.h>
#include <cuda.h>
#include <stdint.h>

typedef __nv_bfloat16 bf16;

constexpr int S_TOK = 2048, DM = 1024, NH = 32, DH = 128, HD = 4096, FF = 3584;
constexpr int NSEG = 64, SEG = 32;

__device__ __align__(1024) bf16 g_qkv[(size_t)S_TOK * 3 * HD];
__device__ __align__(1024) bf16 g_h[(size_t)S_TOK * FF];
__device__ __align__(1024) bf16 g_b[(size_t)S_TOK * DM];
__device__ __align__(1024) bf16 g_o[(size_t)S_TOK * HD];
__device__ float g_gate[S_TOK];
__device__ __align__(1024) uint32_t g_kvmem[NSEG * NH * 2 * 512];
__device__ __align__(1024) uint4 g_xchg[3 * 131072];
__device__ uint32_t g_ptab[96];
enum { C_QF = 0, C_QX = 1, C_QO = 2, C_F1 = 4, C_F2 = 20, C_XA = 36, C_SEG = 52, C_N = 116 };
__device__ uint32_t g_cnt[C_N * 32];

__device__ __forceinline__ uint32_t smem_u32(const void* p) { return (uint32_t)__cvta_generic_to_shared(p); }
__device__ __forceinline__ void mbar_init(uint32_t bar, uint32_t cnt) {
    asm volatile("mbarrier.init.shared::cta.b64 [%0], %1;" ::"r"(bar), "r"(cnt) : "memory");
}
__device__ __forceinline__ void mbar_expect_tx(uint32_t bar, uint32_t bytes) {
    asm volatile("mbarrier.arrive.expect_tx.shared::cta.b64 _, [%0], %1;" ::"r"(bar), "r"(bytes) : "memory");
}
__device__ __forceinline__ void mbar_arrive(uint32_t bar) {
    asm volatile("mbarrier.arrive.shared::cta.b64 _, [%0];" ::"r"(bar) : "memory");
}
__device__ __forceinline__ bool mbar_try(uint32_t bar, uint32_t parity) {
    uint32_t ok;
    asm volatile("{.reg .pred p; mbarrier.try_wait.parity.shared::cta.b64 p, [%1], %2; selp.u32 %0, 1, 0, p;}"
                 : "=r"(ok) : "r"(bar), "r"(parity) : "memory");
    return ok;
}
__device__ __forceinline__ void mbar_wait(uint32_t bar, uint32_t parity) {
    if (mbar_try(bar, parity)) return;
#pragma unroll 1
    for (uint32_t i = 0; i < (1u << 22); i++)
        if (mbar_try(bar, parity)) return;
    __trap();
}
__device__ __forceinline__ void tma_load_2d(uint32_t dst, const CUtensorMap* tm, int c0, int c1, uint32_t bar) {
    asm volatile("cp.async.bulk.tensor.2d.shared::cluster.global.mbarrier::complete_tx::bytes [%0], [%1, {%3, %4}], [%2];"
                 ::"r"(dst), "l"(tm), "r"(bar), "r"(c0), "r"(c1) : "memory");
}
__device__ __forceinline__ void tma_store_2d(const CUtensorMap* tm, int c0, int c1, uint32_t src) {
    asm volatile("cp.async.bulk.tensor.2d.global.shared::cta.bulk_group [%0, {%2, %3}], [%1];"
                 ::"l"(tm), "r"(src), "r"(c0), "r"(c1) : "memory");
}
__device__ __forceinline__ void bulk_load(uint32_t dst, const void* src, uint32_t bytes, uint32_t bar) {
    asm volatile("cp.async.bulk.shared::cluster.global.mbarrier::complete_tx::bytes [%0], [%1], %2, [%3];"
                 ::"r"(dst), "l"(src), "r"(bytes), "r"(bar) : "memory");
}
__device__ __forceinline__ void bulk_commit() { asm volatile("cp.async.bulk.commit_group;" ::: "memory"); }
__device__ __forceinline__ void bulk_wait_read0() { asm volatile("cp.async.bulk.wait_group.read 0;" ::: "memory"); }
__device__ __forceinline__ void bulk_wait0() { asm volatile("cp.async.bulk.wait_group 0;" ::: "memory"); }
__device__ __forceinline__ void fence_async_smem() { asm volatile("fence.proxy.async.shared::cta;" ::: "memory"); }
__device__ __forceinline__ void bar_sync(int id, int n) { asm volatile("bar.sync %0, %1;" ::"r"(id), "r"(n) : "memory"); }
__device__ __forceinline__ void bar_arrive(int id, int n) { asm volatile("bar.arrive %0, %1;" ::"r"(id), "r"(n) : "memory"); }
__device__ __forceinline__ void wg_fence() { asm volatile("wgmma.fence.sync.aligned;" ::: "memory"); }
__device__ __forceinline__ void wg_commit() { asm volatile("wgmma.commit_group.sync.aligned;" ::: "memory"); }
template <int N> __device__ __forceinline__ void wg_wait() { asm volatile("wgmma.wait_group.sync.aligned %0;" ::"n"(N) : "memory"); }
template <int N> __device__ __forceinline__ void reg_inc() { asm volatile("setmaxnreg.inc.sync.aligned.u32 %0;" ::"n"(N)); }
template <int N> __device__ __forceinline__ void reg_dec() { asm volatile("setmaxnreg.dec.sync.aligned.u32 %0;" ::"n"(N)); }
__device__ __forceinline__ uint64_t make_desc(uint32_t saddr, uint32_t lbo, uint32_t sbo, uint32_t swz) {
    return (uint64_t)((saddr & 0x3FFFF) >> 4) | ((uint64_t)(lbo >> 4) << 16) | ((uint64_t)(sbo >> 4) << 32) | ((uint64_t)swz << 62);
}
__device__ __forceinline__ uint32_t pack_bf16(float lo, float hi) {
    uint32_t r;
    asm("cvt.rn.bf16x2.f32 %0, %1, %2;" : "=r"(r) : "f"(hi), "f"(lo));
    return r;
}
__device__ __forceinline__ float bf_lo(uint32_t v) { return __uint_as_float(v << 16); }
__device__ __forceinline__ float bf_hi(uint32_t v) { return __uint_as_float(v & 0xFFFF0000u); }
__device__ __forceinline__ void ldsm4(uint32_t* r, uint32_t a) {
    asm volatile("ldmatrix.sync.aligned.m8n8.x4.shared.b16 {%0,%1,%2,%3}, [%4];"
                 : "=r"(r[0]), "=r"(r[1]), "=r"(r[2]), "=r"(r[3]) : "r"(a) : "memory");
}
__device__ __forceinline__ void ldsm4t(uint32_t* r, uint32_t a) {
    asm volatile("ldmatrix.sync.aligned.m8n8.x4.trans.shared.b16 {%0,%1,%2,%3}, [%4];"
                 : "=r"(r[0]), "=r"(r[1]), "=r"(r[2]), "=r"(r[3]) : "r"(a) : "memory");
}
__device__ __forceinline__ void stsm4(uint32_t a, uint32_t r0, uint32_t r1, uint32_t r2, uint32_t r3) {
    asm volatile("stmatrix.sync.aligned.m8n8.x4.shared.b16 [%0], {%1,%2,%3,%4};"
                 ::"r"(a), "r"(r0), "r"(r1), "r"(r2), "r"(r3) : "memory");
}
__device__ __forceinline__ void mma16816(float* d, uint32_t a0, uint32_t a1, uint32_t a2, uint32_t a3, uint32_t b0, uint32_t b1) {
    asm volatile("mma.sync.aligned.m16n8k16.row.col.f32.bf16.bf16.f32 {%0,%1,%2,%3}, {%4,%5,%6,%7}, {%8,%9}, {%0,%1,%2,%3};"
                 : "+f"(d[0]), "+f"(d[1]), "+f"(d[2]), "+f"(d[3])
                 : "r"(a0), "r"(a1), "r"(a2), "r"(a3), "r"(b0), "r"(b1));
}
__device__ __forceinline__ void mma1688(float* d, uint32_t a0, uint32_t a1, uint32_t b0) {
    asm volatile("mma.sync.aligned.m16n8k8.row.col.f32.bf16.bf16.f32 {%0,%1,%2,%3}, {%4,%5}, {%6}, {%0,%1,%2,%3};"
                 : "+f"(d[0]), "+f"(d[1]), "+f"(d[2]), "+f"(d[3])
                 : "r"(a0), "r"(a1), "r"(b0));
}
__device__ __forceinline__ uint4 ld_relaxed128(const void* p) {
    uint4 v;
    asm volatile("ld.relaxed.gpu.global.L1::no_allocate.v4.u32 {%0,%1,%2,%3}, [%4];" : "=r"(v.x), "=r"(v.y), "=r"(v.z), "=r"(v.w) : "l"(p) : "memory");
    return v;
}
__device__ __forceinline__ void st_relaxed64(void* p, uint32_t a, uint32_t b) {
    asm volatile("st.relaxed.gpu.global.L1::no_allocate.v2.u32 [%0], {%1,%2};" ::"l"(p), "r"(a), "r"(b) : "memory");
}
__device__ __forceinline__ void st_relaxed32(void* p, uint32_t a) {
    asm volatile("st.relaxed.gpu.global.L1::no_allocate.u32 [%0], %1;" ::"l"(p), "r"(a) : "memory");
}
__device__ __forceinline__ void sts128(uint32_t a, uint4 v) {
    asm volatile("st.shared.v4.u32 [%0], {%1,%2,%3,%4};" ::"r"(a), "r"(v.x), "r"(v.y), "r"(v.z), "r"(v.w) : "memory");
}
__device__ __forceinline__ void sts32(uint32_t a, uint32_t v) { asm volatile("st.shared.u32 [%0], %1;" ::"r"(a), "r"(v) : "memory"); }
__device__ __forceinline__ void sts64f(uint32_t a, float x, float y) { asm volatile("st.shared.v2.f32 [%0], {%1,%2};" ::"r"(a), "f"(x), "f"(y) : "memory"); }
__device__ __forceinline__ uint32_t lds32(uint32_t a) { uint32_t v; asm volatile("ld.shared.u32 %0, [%1];" : "=r"(v) : "r"(a) : "memory"); return v; }
__device__ __forceinline__ void lds64f(uint32_t a, float& x, float& y) { asm volatile("ld.shared.v2.f32 {%0,%1}, [%2];" : "=f"(x), "=f"(y) : "r"(a) : "memory"); }
__device__ __forceinline__ uint32_t mapa(uint32_t a, uint32_t r) { uint32_t d; asm volatile("mapa.shared::cluster.u32 %0, %1, %2;" : "=r"(d) : "r"(a), "r"(r)); return d; }
__device__ __forceinline__ void st_async32(uint32_t a, uint32_t v, uint32_t bar) {
    asm volatile("st.async.shared::cluster.mbarrier::complete_tx::bytes.u32 [%0], %1, [%2];" ::"r"(a), "r"(v), "r"(bar) : "memory");
}
__device__ __forceinline__ float ex2(float x) { float y; asm("ex2.approx.ftz.f32 %0, %1;" : "=f"(y) : "f"(x)); return y; }
__device__ __forceinline__ uint32_t clk32() { unsigned long long t; asm volatile("mov.u64 %0, %%clock64;" : "=l"(t)::"memory"); return (uint32_t)t; }

__device__ __forceinline__ void wgmma_ss_n256_t01(float* d, uint64_t da, uint64_t db, int scale_d) {
    asm volatile("{.reg .pred p; setp.ne.b32 p, %130, 0;\n"
        "wgmma.mma_async.sync.aligned.m64n256k16.f32.bf16.bf16 {%0,%1,%2,%3,%4,%5,%6,%7,%8,%9,%10,%11,%12,%13,%14,%15,%16,%17,%18,%19,%20,%21,%22,%23,%24,%25,%26,%27,%28,%29,%30,%31,%32,%33,%34,%35,%36,%37,%38,%39,%40,%41,%42,%43,%44,%45,%46,%47,%48,%49,%50,%51,%52,%53,%54,%55,%56,%57,%58,%59,%60,%61,%62,%63,%64,%65,%66,%67,%68,%69,%70,%71,%72,%73,%74,%75,%76,%77,%78,%79,%80,%81,%82,%83,%84,%85,%86,%87,%88,%89,%90,%91,%92,%93,%94,%95,%96,%97,%98,%99,%100,%101,%102,%103,%104,%105,%106,%107,%108,%109,%110,%111,%112,%113,%114,%115,%116,%117,%118,%119,%120,%121,%122,%123,%124,%125,%126,%127}, %128, %129, p, 1, 1, 0, 1;}"
        : "+f"(d[0]), "+f"(d[1]), "+f"(d[2]), "+f"(d[3]), "+f"(d[4]), "+f"(d[5]), "+f"(d[6]), "+f"(d[7]), "+f"(d[8]), "+f"(d[9]), "+f"(d[10]), "+f"(d[11]), "+f"(d[12]), "+f"(d[13]), "+f"(d[14]), "+f"(d[15]), "+f"(d[16]), "+f"(d[17]), "+f"(d[18]), "+f"(d[19]), "+f"(d[20]), "+f"(d[21]), "+f"(d[22]), "+f"(d[23]), "+f"(d[24]), "+f"(d[25]), "+f"(d[26]), "+f"(d[27]), "+f"(d[28]), "+f"(d[29]), "+f"(d[30]), "+f"(d[31]), "+f"(d[32]), "+f"(d[33]), "+f"(d[34]), "+f"(d[35]), "+f"(d[36]), "+f"(d[37]), "+f"(d[38]), "+f"(d[39]), "+f"(d[40]), "+f"(d[41]), "+f"(d[42]), "+f"(d[43]), "+f"(d[44]), "+f"(d[45]), "+f"(d[46]), "+f"(d[47]), "+f"(d[48]), "+f"(d[49]), "+f"(d[50]), "+f"(d[51]), "+f"(d[52]), "+f"(d[53]), "+f"(d[54]), "+f"(d[55]), "+f"(d[56]), "+f"(d[57]), "+f"(d[58]), "+f"(d[59]), "+f"(d[60]), "+f"(d[61]), "+f"(d[62]), "+f"(d[63]), "+f"(d[64]), "+f"(d[65]), "+f"(d[66]), "+f"(d[67]), "+f"(d[68]), "+f"(d[69]), "+f"(d[70]), "+f"(d[71]), "+f"(d[72]), "+f"(d[73]), "+f"(d[74]), "+f"(d[75]), "+f"(d[76]), "+f"(d[77]), "+f"(d[78]), "+f"(d[79]), "+f"(d[80]), "+f"(d[81]), "+f"(d[82]), "+f"(d[83]), "+f"(d[84]), "+f"(d[85]), "+f"(d[86]), "+f"(d[87]), "+f"(d[88]), "+f"(d[89]), "+f"(d[90]), "+f"(d[91]), "+f"(d[92]), "+f"(d[93]), "+f"(d[94]), "+f"(d[95]), "+f"(d[96]), "+f"(d[97]), "+f"(d[98]), "+f"(d[99]), "+f"(d[100]), "+f"(d[101]), "+f"(d[102]), "+f"(d[103]), "+f"(d[104]), "+f"(d[105]), "+f"(d[106]), "+f"(d[107]), "+f"(d[108]), "+f"(d[109]), "+f"(d[110]), "+f"(d[111]), "+f"(d[112]), "+f"(d[113]), "+f"(d[114]), "+f"(d[115]), "+f"(d[116]), "+f"(d[117]), "+f"(d[118]), "+f"(d[119]), "+f"(d[120]), "+f"(d[121]), "+f"(d[122]), "+f"(d[123]), "+f"(d[124]), "+f"(d[125]), "+f"(d[126]), "+f"(d[127])
        : "l"(da), "l"(db), "r"(scale_d));
}
__device__ __forceinline__ void wgmma_ss_n128_t01(float* d, uint64_t da, uint64_t db, int scale_d) {
    asm volatile("{.reg .pred p; setp.ne.b32 p, %66, 0;\n"
        "wgmma.mma_async.sync.aligned.m64n128k16.f32.bf16.bf16 {%0,%1,%2,%3,%4,%5,%6,%7,%8,%9,%10,%11,%12,%13,%14,%15,%16,%17,%18,%19,%20,%21,%22,%23,%24,%25,%26,%27,%28,%29,%30,%31,%32,%33,%34,%35,%36,%37,%38,%39,%40,%41,%42,%43,%44,%45,%46,%47,%48,%49,%50,%51,%52,%53,%54,%55,%56,%57,%58,%59,%60,%61,%62,%63}, %64, %65, p, 1, 1, 0, 1;}"
        : "+f"(d[0]), "+f"(d[1]), "+f"(d[2]), "+f"(d[3]), "+f"(d[4]), "+f"(d[5]), "+f"(d[6]), "+f"(d[7]), "+f"(d[8]), "+f"(d[9]), "+f"(d[10]), "+f"(d[11]), "+f"(d[12]), "+f"(d[13]), "+f"(d[14]), "+f"(d[15]), "+f"(d[16]), "+f"(d[17]), "+f"(d[18]), "+f"(d[19]), "+f"(d[20]), "+f"(d[21]), "+f"(d[22]), "+f"(d[23]), "+f"(d[24]), "+f"(d[25]), "+f"(d[26]), "+f"(d[27]), "+f"(d[28]), "+f"(d[29]), "+f"(d[30]), "+f"(d[31]), "+f"(d[32]), "+f"(d[33]), "+f"(d[34]), "+f"(d[35]), "+f"(d[36]), "+f"(d[37]), "+f"(d[38]), "+f"(d[39]), "+f"(d[40]), "+f"(d[41]), "+f"(d[42]), "+f"(d[43]), "+f"(d[44]), "+f"(d[45]), "+f"(d[46]), "+f"(d[47]), "+f"(d[48]), "+f"(d[49]), "+f"(d[50]), "+f"(d[51]), "+f"(d[52]), "+f"(d[53]), "+f"(d[54]), "+f"(d[55]), "+f"(d[56]), "+f"(d[57]), "+f"(d[58]), "+f"(d[59]), "+f"(d[60]), "+f"(d[61]), "+f"(d[62]), "+f"(d[63])
        : "l"(da), "l"(db), "r"(scale_d));
}
__device__ __forceinline__ void wgmma_ss_n32_t10(float* d, uint64_t da, uint64_t db, int scale_d) {
    asm volatile("{.reg .pred p; setp.ne.b32 p, %18, 0;\n"
        "wgmma.mma_async.sync.aligned.m64n32k16.f32.bf16.bf16 {%0,%1,%2,%3,%4,%5,%6,%7,%8,%9,%10,%11,%12,%13,%14,%15}, %16, %17, p, 1, 1, 1, 0;}"
        : "+f"(d[0]), "+f"(d[1]), "+f"(d[2]), "+f"(d[3]), "+f"(d[4]), "+f"(d[5]), "+f"(d[6]), "+f"(d[7]), "+f"(d[8]), "+f"(d[9]), "+f"(d[10]), "+f"(d[11]), "+f"(d[12]), "+f"(d[13]), "+f"(d[14]), "+f"(d[15])
        : "l"(da), "l"(db), "r"(scale_d));
}
__device__ __forceinline__ void wgmma_ss_n40_t10(float* d, uint64_t da, uint64_t db, int scale_d) {
    asm volatile("{.reg .pred p; setp.ne.b32 p, %22, 0;\n"
        "wgmma.mma_async.sync.aligned.m64n40k16.f32.bf16.bf16 {%0,%1,%2,%3,%4,%5,%6,%7,%8,%9,%10,%11,%12,%13,%14,%15,%16,%17,%18,%19}, %20, %21, p, 1, 1, 1, 0;}"
        : "+f"(d[0]), "+f"(d[1]), "+f"(d[2]), "+f"(d[3]), "+f"(d[4]), "+f"(d[5]), "+f"(d[6]), "+f"(d[7]), "+f"(d[8]), "+f"(d[9]), "+f"(d[10]), "+f"(d[11]), "+f"(d[12]), "+f"(d[13]), "+f"(d[14]), "+f"(d[15]), "+f"(d[16]), "+f"(d[17]), "+f"(d[18]), "+f"(d[19])
        : "l"(da), "l"(db), "r"(scale_d));
}
__device__ __forceinline__ void wgmma_rs_n32_t0(float* d, const uint32_t* a, uint64_t db, int scale_d) {
    asm volatile("{.reg .pred p; setp.ne.b32 p, %21, 0;\n"
        "wgmma.mma_async.sync.aligned.m64n32k16.f32.bf16.bf16 {%0,%1,%2,%3,%4,%5,%6,%7,%8,%9,%10,%11,%12,%13,%14,%15}, {%16,%17,%18,%19}, %20, p, 1, 1, 0;}"
        : "+f"(d[0]), "+f"(d[1]), "+f"(d[2]), "+f"(d[3]), "+f"(d[4]), "+f"(d[5]), "+f"(d[6]), "+f"(d[7]), "+f"(d[8]), "+f"(d[9]), "+f"(d[10]), "+f"(d[11]), "+f"(d[12]), "+f"(d[13]), "+f"(d[14]), "+f"(d[15])
        : "r"(a[0]), "r"(a[1]), "r"(a[2]), "r"(a[3]), "l"(db), "r"(scale_d));
}

__global__ void __launch_bounds__(256) prep_kernel(const bf16* __restrict__ x, const bf16* __restrict__ gw, uint4* xchg) {
    int warp = threadIdx.x >> 5, lane = threadIdx.x & 31;
    int row = blockIdx.x * 8 + warp;
    const uint4* xr = (const uint4*)(x + (size_t)row * DM);
    const uint4* gr = (const uint4*)gw;
    float acc = 0.f;
#pragma unroll
    for (int i = 0; i < 4; i++) {
        uint4 a = xr[i * 32 + lane], b = gr[i * 32 + lane];
        acc += bf_lo(a.x) * bf_lo(b.x) + bf_hi(a.x) * bf_hi(b.x) + bf_lo(a.y) * bf_lo(b.y) + bf_hi(a.y) * bf_hi(b.y);
        acc += bf_lo(a.z) * bf_lo(b.z) + bf_hi(a.z) * bf_hi(b.z) + bf_lo(a.w) * bf_lo(b.w) + bf_hi(a.w) * bf_hi(b.w);
    }
#pragma unroll
    for (int o = 16; o > 0; o >>= 1) acc += __shfl_xor_sync(~0u, acc, o);
    if (lane == 0) g_gate[row] = 1.f / (1.f + __expf(-acc));
    int gid = blockIdx.x * 256 + threadIdx.x;
    xchg[gid] = make_uint4(~0u, ~0u, ~0u, ~0u);
    xchg[gid + 65536] = make_uint4(~0u, ~0u, ~0u, ~0u);
    xchg[gid + 131072] = make_uint4(0, 0, 0, 0);
    xchg[gid + 196608] = make_uint4(0, 0, 0, 0);
    if (gid < 96) g_ptab[gid] = 0;
    if (gid < C_N) g_cnt[gid * 32] = 0;
}

constexpr float SM_SCALE_LOG2 = 0.08838834764831845f * 1.4426950408889634f;
__device__ __forceinline__ void stsm4t(uint32_t a, uint32_t r0, uint32_t r1, uint32_t r2, uint32_t r3) {
    asm volatile("stmatrix.sync.aligned.m8n8.x4.trans.shared.b16 [%0], {%1,%2,%3,%4};"
                 ::"r"(a), "r"(r0), "r"(r1), "r"(r2), "r"(r3) : "memory");
}
__device__ __forceinline__ void xattn_warp(int seg, int head, int lane, uint32_t so, const CUtensorMap* tmO) {
    const uint4* q = (const uint4*)g_qkv + (size_t)(seg * NH + head) * 1536 + lane;
    const uint2* km = (const uint2*)g_kvmem + (size_t)(seg * NH + head) * 512 + lane;
    float s0[3][4], s1[5][4];
#pragma unroll
    for (int j = 0; j < 3; j++) s0[j][0] = s0[j][1] = s0[j][2] = s0[j][3] = 0.f;
#pragma unroll
    for (int j = 0; j < 5; j++) s1[j][0] = s1[j][1] = s1[j][2] = s1[j][3] = 0.f;
#pragma unroll
    for (int k = 0; k < 8; k++) {
        const uint4 a0 = __ldcg(q + k * 32), a1 = __ldcg(q + 256 + k * 32);
        const uint4 k0 = __ldcg(q + 512 + k * 32), k1 = __ldcg(q + 768 + k * 32);
        const uint2 m = __ldcg(km + k * 32);
        mma16816(s0[0], a0.x, a0.y, a0.z, a0.w, k0.x, k0.y);
        mma16816(s0[1], a0.x, a0.y, a0.z, a0.w, k0.z, k0.w);
        mma16816(s0[2], a0.x, a0.y, a0.z, a0.w, m.x, m.y);
        mma16816(s1[0], a1.x, a1.y, a1.z, a1.w, k0.x, k0.y);
        mma16816(s1[1], a1.x, a1.y, a1.z, a1.w, k0.z, k0.w);
        mma16816(s1[2], a1.x, a1.y, a1.z, a1.w, k1.x, k1.y);
        mma16816(s1[3], a1.x, a1.y, a1.z, a1.w, k1.z, k1.w);
        mma16816(s1[4], a1.x, a1.y, a1.z, a1.w, m.x, m.y);
    }
    const int g = lane >> 2, t2 = (lane & 3) * 2;
    const bool d0 = t2 > g, d1 = t2 + 1 > g;
    if (d0) { s0[0][0] = -INFINITY; s0[1][2] = -INFINITY; s1[2][0] = -INFINITY; s1[3][2] = -INFINITY; }
    if (d1) { s0[0][1] = -INFINITY; s0[1][3] = -INFINITY; s1[2][1] = -INFINITY; s1[3][3] = -INFINITY; }
    s0[1][0] = s0[1][1] = -INFINITY;
    s1[3][0] = s1[3][1] = -INFINITY;
    uint32_t p0[2][3], p1[2][5];
#pragma unroll
    for (int h = 0; h < 2; h++) {
        float m = -INFINITY, n = -INFINITY;
#pragma unroll
        for (int j = 0; j < 3; j++) m = fmaxf(m, fmaxf(s0[j][2 * h], s0[j][2 * h + 1]));
#pragma unroll
        for (int j = 0; j < 5; j++) n = fmaxf(n, fmaxf(s1[j][2 * h], s1[j][2 * h + 1]));
        m = fmaxf(m, __shfl_xor_sync(~0u, m, 1)); n = fmaxf(n, __shfl_xor_sync(~0u, n, 1));
        m = fmaxf(m, __shfl_xor_sync(~0u, m, 2)); n = fmaxf(n, __shfl_xor_sync(~0u, n, 2));
        float lm = 0.f, ln = 0.f;
#pragma unroll
        for (int j = 0; j < 3; j++) {
            s0[j][2 * h] = ex2((s0[j][2 * h] - m) * SM_SCALE_LOG2); s0[j][2 * h + 1] = ex2((s0[j][2 * h + 1] - m) * SM_SCALE_LOG2);
            lm += s0[j][2 * h] + s0[j][2 * h + 1];
        }
#pragma unroll
        for (int j = 0; j < 5; j++) {
            s1[j][2 * h] = ex2((s1[j][2 * h] - n) * SM_SCALE_LOG2); s1[j][2 * h + 1] = ex2((s1[j][2 * h + 1] - n) * SM_SCALE_LOG2);
            ln += s1[j][2 * h] + s1[j][2 * h + 1];
        }
        lm += __shfl_xor_sync(~0u, lm, 1); ln += __shfl_xor_sync(~0u, ln, 1);
        lm += __shfl_xor_sync(~0u, lm, 2); ln += __shfl_xor_sync(~0u, ln, 2);
        lm = 1.f / lm; ln = 1.f / ln;
#pragma unroll
        for (int j = 0; j < 3; j++) p0[h][j] = pack_bf16(s0[j][2 * h] * lm, s0[j][2 * h + 1] * lm);
#pragma unroll
        for (int j = 0; j < 5; j++) p1[h][j] = pack_bf16(s1[j][2 * h] * ln, s1[j][2 * h + 1] * ln);
    }
    const int row = (lane >> 4) * 8 + (lane & 7), hb = (lane >> 3) & 1;
#pragma unroll
    for (int w = 0; w < 8; w++) {
        const uint4 v0 = __ldcg(q + 1024 + w * 32), v1 = __ldcg(q + 1280 + w * 32);
        const uint2 m = __ldcg(km + 256 + w * 32);
        float o[4][4];
#pragma unroll
        for (int j = 0; j < 4; j++) o[j][0] = o[j][1] = o[j][2] = o[j][3] = 0.f;
#pragma unroll
        for (int h = 0; h < 2; h++) {
            mma16816(o[h], v0.x, v0.y, v0.z, v0.w, p0[h][0], p0[h][1]);
            mma16816(o[2 + h], v0.x, v0.y, v0.z, v0.w, p1[h][0], p1[h][1]);
            mma16816(o[2 + h], v1.x, v1.y, v1.z, v1.w, p1[h][2], p1[h][3]);
            mma1688(o[h], m.x, m.y, p0[h][2]);
            mma1688(o[2 + h], m.x, m.y, p1[h][4]);
        }
        if ((w & 3) == 0) {
            if (lane == 0) bulk_wait_read0();
            __syncwarp();
        }
        const uint32_t a = so + row * 128 + ((((w & 3) * 2 + hb) ^ (row & 7)) << 4);
        stsm4t(a, pack_bf16(o[0][0], o[0][1]), pack_bf16(o[0][2], o[0][3]), pack_bf16(o[1][0], o[1][1]), pack_bf16(o[1][2], o[1][3]));
        stsm4t(a + 2048, pack_bf16(o[2][0], o[2][1]), pack_bf16(o[2][2], o[2][3]), pack_bf16(o[3][0], o[3][1]), pack_bf16(o[3][2], o[3][3]));
        if ((w & 3) == 3) {
            fence_async_smem();
            __syncwarp();
            if (lane == 0) { tma_store_2d(tmO, head * 128 + (w >> 2) * 64, seg * SEG, so); bulk_commit(); }
        }
    }
}

enum { T_FFN1 = 0, T_FFN2 = 1, T_OPROJ = 2, T_XATT = 3, T_DONE = 4 };
struct WorkParams {
    CUtensorMap tmA[3], tmB[3], tmC[3];
    CUtensorMap tmO32;
    const bf16* bias[2];
};
constexpr int WK_STAGE = 49152, WK_NST = 4;
constexpr int WK_SMEM = WK_NST * WK_STAGE + 32768 + 256 + 1024;
constexpr int NQF = 224 + 64;

__device__ __forceinline__ uint32_t ld_acquire(const uint32_t* p) {
    uint32_t v;
    asm volatile("ld.acquire.gpu.global.u32 %0, [%1];" : "=r"(v) : "l"(p) : "memory");
    return v;
}
__device__ __forceinline__ uint32_t ld_relaxed32(const uint32_t* p) {
    uint32_t v;
    asm volatile("ld.relaxed.gpu.global.u32 %0, [%1];" : "=r"(v) : "l"(p) : "memory");
    return v;
}
__device__ __forceinline__ void signal_cnt(int c) {
    asm volatile("red.release.gpu.global.add.u32 [%0], 1;" ::"l"(&g_cnt[c * 32]) : "memory");
}
__device__ __forceinline__ uint32_t ffn_task(int f) {
    if (f < 42) return T_FFN1 | ((f / 14) << 8) | ((f % 14) << 16);
    f -= 42;
    if (f < 13 * 18) {
        const int g = f / 18, r = f % 18;
        return r < 14 ? (T_FFN1 | ((g + 3) << 8) | (r << 16)) : (T_FFN2 | (g << 8) | ((r - 14) << 16));
    }
    f -= 13 * 18;
    return T_FFN2 | ((13 + (f >> 2)) << 8) | ((f & 3) << 16);
}
__device__ __forceinline__ void wait_cnt(int c, uint32_t v) {
    uint32_t n = 0;
    while (ld_acquire(&g_cnt[c * 32]) != v) { __nanosleep(64); if (++n > (1u << 24)) __trap(); }
}
__device__ __forceinline__ uint32_t pick_task(bool& ffn_left) {
    for (uint32_t it = 0; it < (1u << 24); it++) {
        uint32_t x = ld_relaxed32(&g_cnt[C_QX * 32]);
        if (x < 256) {
            bool got = false;
            if (ld_relaxed32(&g_cnt[(C_SEG + NSEG - 1) * 32]) == 96) { x = atomicAdd(&g_cnt[C_QX * 32], 1); got = x < 256; }
            else if (ld_relaxed32(&g_cnt[(C_SEG + (x >> 2)) * 32]) == 96) got = atomicCAS(&g_cnt[C_QX * 32], x, x + 1) == x;
            if (got) { wait_cnt(C_SEG + (x >> 2), 96); return T_XATT | ((x >> 2) << 8) | ((x & 3) << 16); }
        }
        if (ffn_left) {
            const uint32_t f = atomicAdd(&g_cnt[C_QF * 32], 1);
            if (f < NQF) {
                const uint32_t t = ffn_task(f);
                if ((t & 255) == T_FFN2) wait_cnt(C_F1 + ((t >> 8) & 255), 28);
                return t;
            }
            ffn_left = false;
        }
        uint32_t o = ld_relaxed32(&g_cnt[C_QO * 32]);
        if (o >= 128) return T_DONE;
        bool got = false;
        if (x >= 256) { o = atomicAdd(&g_cnt[C_QO * 32], 1); got = o < 128; }
        else if (ld_relaxed32(&g_cnt[(C_XA + (o >> 3)) * 32]) == 128 && ld_relaxed32(&g_cnt[(C_F2 + (o >> 3)) * 32]) == 8)
            got = atomicCAS(&g_cnt[C_QO * 32], o, o + 1) == o;
        if (got) {
            wait_cnt(C_XA + (o >> 3), 128);
            wait_cnt(C_F2 + (o >> 3), 8);
            return T_OPROJ | ((o >> 3) << 8) | ((o & 7) << 16);
        }
        __nanosleep(200);
    }
    __trap();
    return T_DONE;
}

template <int TYPE>
__device__ __forceinline__ void gemm_tile(const WorkParams& p, uint32_t sb, uint32_t bars, uint32_t stg, int m0, int nb, int cw, int warp, int lane,
                                          bool leader, int& st, int& ph, int& dph) {
    constexpr int BN = TYPE == T_OPROJ ? 128 : 256;
    constexpr int KB = TYPE == T_FFN1 ? 16 : (TYPE == T_FFN2 ? 56 : 64);
    const int n0 = nb * BN;
    float acc[BN / 2];
#pragma unroll
    for (int i = 0; i < BN / 2; i++) acc[i] = 0.f;
    if (TYPE == T_OPROJ) {
        if (lane == 0) bulk_wait_read0();
        bar_sync(1 + cw, 128);
        if (leader) {
            asm volatile("fence.proxy.async.global;" ::: "memory");
            mbar_expect_tx(bars + 64 + 8 * cw, 16384);
            tma_load_2d(stg, &p.tmC[T_FFN2], n0, m0 + cw * 64, bars + 64 + 8 * cw);
            tma_load_2d(stg + 8192, &p.tmC[T_FFN2], n0 + 64, m0 + cw * 64, bars + 64 + 8 * cw);
        }
    }
    int prev = 0;
    for (int kb = 0; kb < KB; kb++) {
        mbar_wait(bars + 8 * st, ph);
        const uint32_t a = sb + st * WK_STAGE;
        const uint64_t da = make_desc(a + cw * 8192, 16, 1024, 1);
        const uint64_t db = make_desc(a + 16384, 8192, 1024, 1);
        wg_fence();
#pragma unroll
        for (int k = 0; k < 4; k++) {
            if (BN == 256) wgmma_ss_n256_t01(acc, da + k * 2, db + k * 128, (kb | k) != 0);
            else wgmma_ss_n128_t01(acc, da + k * 2, db + k * 128, (kb | k) != 0);
        }
        wg_commit();
        if (kb > 0) { wg_wait<1>(); if (leader) mbar_arrive(bars + 32 + 8 * prev); }
        prev = st;
        if (++st == WK_NST) { st = 0; ph ^= 1; }
    }
    wg_wait<0>();
    if (leader) mbar_arrive(bars + 32 + 8 * prev);
    const int g = lane >> 2, t = lane & 3;
    const int srow = warp * 16 + ((lane >> 3) & 1) * 8 + (lane & 7);
    float g0 = 0.f, g1 = 0.f;
    if (TYPE == T_OPROJ) {
        g0 = g_gate[m0 + cw * 64 + warp * 16 + g];
        g1 = g_gate[m0 + cw * 64 + warp * 16 + g + 8];
        mbar_wait(bars + 64 + 8 * cw, dph);
        dph ^= 1;
    }
#pragma unroll
    for (int r = 0; r < BN / 128; r++) {
        if (TYPE != T_OPROJ) {
            if (lane == 0) bulk_wait_read0();
            bar_sync(1 + cw, 128);
        }
#pragma unroll
        for (int j = 0; j < 16; j += 2) {
            float v[8];
#pragma unroll
            for (int i = 0; i < 8; i++) v[i] = acc[(r * 16 + j) * 4 + i];
            const int tl = j + (lane >> 4);
            const uint32_t addr = stg + (tl >> 3) * 8192 + srow * 128 + (((tl & 7) ^ (srow & 7)) << 4);
            if (TYPE != T_OPROJ) {
                const bf16* bias = p.bias[TYPE == T_FFN1 ? 0 : 1];
                const uint32_t b0 = *(const uint32_t*)(bias + n0 + r * 128 + j * 8 + 2 * t);
                const uint32_t b1 = *(const uint32_t*)(bias + n0 + r * 128 + j * 8 + 8 + 2 * t);
                v[0] += bf_lo(b0); v[1] += bf_hi(b0); v[2] += bf_lo(b0); v[3] += bf_hi(b0);
                v[4] += bf_lo(b1); v[5] += bf_hi(b1); v[6] += bf_lo(b1); v[7] += bf_hi(b1);
                if (TYPE == T_FFN1) {
#pragma unroll
                    for (int i = 0; i < 8; i++) { const float q = v[i] > 0.f ? v[i] : 0.f; v[i] = q * q; }
                }
            } else {
                uint32_t d[4];
                ldsm4(d, addr);
                v[0] = g0 * v[0] + (1.f - g0) * bf_lo(d[0]); v[1] = g0 * v[1] + (1.f - g0) * bf_hi(d[0]);
                v[2] = g1 * v[2] + (1.f - g1) * bf_lo(d[1]); v[3] = g1 * v[3] + (1.f - g1) * bf_hi(d[1]);
                v[4] = g0 * v[4] + (1.f - g0) * bf_lo(d[2]); v[5] = g0 * v[5] + (1.f - g0) * bf_hi(d[2]);
                v[6] = g1 * v[6] + (1.f - g1) * bf_lo(d[3]); v[7] = g1 * v[7] + (1.f - g1) * bf_hi(d[3]);
            }
            stsm4(addr, pack_bf16(v[0], v[1]), pack_bf16(v[2], v[3]), pack_bf16(v[4], v[5]), pack_bf16(v[6], v[7]));
        }
        fence_async_smem();
        bar_sync(1 + cw, 128);
        if (leader) {
            tma_store_2d(&p.tmC[TYPE], n0 + r * 128, m0 + cw * 64, stg);
            tma_store_2d(&p.tmC[TYPE], n0 + r * 128 + 64, m0 + cw * 64, stg + 8192);
            bulk_commit();
        }
    }
}

__global__ void __launch_bounds__(384, 1) worker_kernel(const __grid_constant__ WorkParams p) {
    extern __shared__ uint8_t smem_raw[];
    const uint32_t sb = (smem_u32(smem_raw) + 1023) & ~1023u;
    const uint32_t s_stg = sb + WK_NST * WK_STAGE;
    const uint32_t bars = s_stg + 32768;
    const int tid = threadIdx.x, wg = tid >> 7, lane = tid & 31;
    if (tid == 0) {
        for (int i = 0; i < WK_NST; i++) { mbar_init(bars + 8 * i, 1); mbar_init(bars + 32 + 8 * i, 2); }
        for (int i = 0; i < 2; i++) { mbar_init(bars + 64 + 8 * i, 1); mbar_init(bars + 80 + 8 * i, 1); mbar_init(bars + 96 + 8 * i, 8); }
        asm volatile("fence.mbarrier_init.release.cluster;" ::: "memory");
    }
    __syncthreads();
    if (wg == 0) {
        reg_dec<40>();
        if (tid == 0) {
            int st = 0, ph = 1;
            bool ffn_left = true;
            for (uint32_t n = 0;; n++) {
                mbar_wait(bars + 96 + 8 * (n & 1), ((n >> 1) & 1) ^ 1);
                const uint32_t task = pick_task(ffn_left);
                sts32(bars + 112 + 4 * (n & 1), task);
                mbar_arrive(bars + 80 + 8 * (n & 1));
                const int type = task & 255;
                if (type == T_DONE) break;
                if (type == T_XATT) continue;
                asm volatile("fence.proxy.async.global;" ::: "memory");
                const int m0 = ((task >> 8) & 255) * 128, nbx = type == T_OPROJ ? 2 : 4, n0 = (task >> 16) * nbx * 64;
                const int kbs = type == T_FFN1 ? 16 : (type == T_FFN2 ? 56 : 64);
                const CUtensorMap* ta = &p.tmA[type];
                const CUtensorMap* tb = &p.tmB[type];
                for (int kb = 0; kb < kbs; kb++) {
                    mbar_wait(bars + 32 + 8 * st, ph);
                    const uint32_t a = sb + st * WK_STAGE, fb = bars + 8 * st;
                    mbar_expect_tx(fb, 16384 + nbx * 8192);
                    tma_load_2d(a, ta, kb * 64, m0, fb);
                    for (int j = 0; j < nbx; j++) tma_load_2d(a + 16384 + j * 8192, tb, n0 + j * 64, kb * 64, fb);
                    if (++st == WK_NST) { st = 0; ph ^= 1; }
                }
            }
        }
    } else {
        reg_inc<232>();
        const int cw = wg - 1, warp = (tid >> 5) & 3;
        const bool leader = (tid & 127) == 0;
        const uint32_t stg = s_stg + cw * 16384;
        int st = 0, ph = 0, dph = 0;
        int pend = -1;
        for (uint32_t n = 0;; n++) {
            if (pend >= 0 && !mbar_try(bars + 80 + 8 * (n & 1), (n >> 1) & 1)) {
                bulk_wait0(); signal_cnt(pend); pend = -1;
            }
            mbar_wait(bars + 80 + 8 * (n & 1), (n >> 1) & 1);
            const uint32_t task = lds32(bars + 112 + 4 * (n & 1));
            __syncwarp();
            if (lane == 0) mbar_arrive(bars + 96 + 8 * (n & 1));
            const int type = task & 255, mb = (task >> 8) & 255, nb = task >> 16;
            if (pend >= 0) { bulk_wait0(); signal_cnt(pend); pend = -1; }
            __syncwarp();
            if (type == T_DONE) break;
            if (type == T_FFN1) { gemm_tile<T_FFN1>(p, sb, bars, stg, mb * 128, nb, cw, warp, lane, leader, st, ph, dph); if (leader) pend = C_F1 + mb; }
            else if (type == T_FFN2) { gemm_tile<T_FFN2>(p, sb, bars, stg, mb * 128, nb, cw, warp, lane, leader, st, ph, dph); if (leader) pend = C_F2 + mb; }
            else if (type == T_OPROJ) gemm_tile<T_OPROJ>(p, sb, bars, stg, mb * 128, nb, cw, warp, lane, leader, st, ph, dph);
            else {
                if (lane == 0) bulk_wait_read0();
                bar_sync(1 + cw, 128);
                xattn_warp(mb, nb * 8 + cw * 4 + warp, lane, stg + warp * 4096, &p.tmO32);
                if (lane == 0) pend = C_XA + (mb >> 2);
            }
        }
        if (lane == 0) bulk_wait0();
        asm volatile("griddepcontrol.wait;" ::: "memory");
    }
}

struct ChainParams {
    CUtensorMap tmW[3];
    CUtensorMap tmWo;
    CUtensorMap tmX;
    const bf16* mem0;
    char* xmem;
    char* xpart;
};
constexpr uint32_t SB = 1024;
constexpr uint32_t CH_WS = SB;
constexpr uint32_t CH_WO = CH_WS + 65536;
constexpr uint32_t CH_W2 = CH_WO + 90112;
constexpr uint32_t CH_RING = CH_W2 + 8192;
constexpr uint32_t CH_MEMR = CH_RING + 24576;
constexpr uint32_t CH_KX = CH_MEMR + 12288;
constexpr uint32_t CH_VX = CH_KX + 8192;
constexpr uint32_t CH_QKV = CH_VX + 8192;
constexpr uint32_t CH_O = CH_QKV + 6144;
constexpr uint32_t CH_S = CH_O + 2048;
constexpr uint32_t CH_L = CH_RING + 65536;
constexpr uint32_t CH_BAR = CH_L + 64;
constexpr uint32_t CH_TS = CH_BAR + 256;
constexpr int CH_SMEM = CH_TS + 128 - SB;
constexpr uint32_t B_DHOP = CH_BAR, B_KV = CH_BAR + 8, B_WS = CH_BAR + 16, B_WO = CH_BAR + 24, B_PF = CH_BAR + 32, B_PE = CH_BAR + 64;
constexpr uint32_t B_XFA = CH_BAR + 128, B_XFK = CH_BAR + 136, B_XFS = CH_BAR + 144;
constexpr uint32_t B_E1 = CH_BAR + 152, B_E3 = CH_BAR + 160, B_E4 = CH_BAR + 168, B_FREE = CH_BAR + 176;
enum { NB_S0 = 1, NB_S1, NB_S2, NB_W0, NB_W1, NB_W2, NB_M0, NB_M1, NB_X, NB_F };
constexpr uint32_t L2_HASH = 0xB3000;

#define TSTAMP(i)
#define TSTAMPD(i, dep)

__device__ __forceinline__ uint32_t umax4(uint4 v) { return __vimax3_u32(__vimax3_u32(v.x, v.y, v.z), v.w, 0u); }
__device__ __forceinline__ void lds128(uint32_t* r, uint32_t a) {
    asm volatile("ld.shared.v4.u32 {%0,%1,%2,%3}, [%4];" : "=r"(r[0]), "=r"(r[1]), "=r"(r[2]), "=r"(r[3]) : "r"(a) : "memory");
}
__device__ __forceinline__ uint32_t opaque(uint32_t x) { uint32_t y; asm volatile("mov.u32 %0, %1;" : "=r"(y) : "r"(x)); return y; }
__device__ __forceinline__ void delay(uint32_t n, uint32_t cb) {
    if (lds32(cb + CH_BAR + 112) == 0x9e3779b9u) __nanosleep(20);
    const uint32_t t0 = clk32();
    while (clk32() - t0 < n) {}
}
#define DRAIN 0
#define NPROBE 24
#define DLY_R 150
#define DLY_S2 200
#define DLY_S 400
__device__ __forceinline__ uint32_t probe_near(char* page) {
    uint32_t best0 = ~0u, best1 = ~0u;
#pragma unroll 1
    for (int r = 0; r < NPROBE; r++) {
        const uint32_t c0 = clk32();
        uint32_t v;
        asm volatile("atom.relaxed.gpu.global.or.b32 %0, [%1], 0;" : "=r"(v) : "l"(page + (r & 1) * 4096 + ((blockIdx.x + (r >> 1) * 5) & 31) * 128) : "memory");
        if (v == 0x9e3779b9u) __nanosleep(20);
        const uint32_t d = clk32() - c0;
        if (r & 1) best1 = min(best1, d); else best0 = min(best0, d);
    }
    return best1 < best0;
}

__device__ __forceinline__ void ld_relaxed128_if(uint4& v, const void* p, bool pred) {
    asm volatile("{.reg .pred q; setp.ne.u32 q, %5, 0; @q ld.relaxed.gpu.global.L1::no_allocate.v4.u32 {%0,%1,%2,%3}, [%4];}"
                 : "+r"(v.x), "+r"(v.y), "+r"(v.z), "+r"(v.w) : "l"(p), "r"((uint32_t)pred) : "memory");
}
__device__ __forceinline__ uint32_t tagdiff(const uint4& v, uint32_t x) { return ((v.x ^ x) | (v.y ^ x)) | ((v.z ^ x) | (v.w ^ x)); }
__device__ __forceinline__ uint32_t reduce_task(const char* src, char* dst, uint32_t x, bool hi, bool wr) {
    uint4 v0 = ld_relaxed128(src), v1 = ld_relaxed128(src + 1024), v2 = ld_relaxed128(src + 2048), v3 = ld_relaxed128(src + 3072);
    uint32_t it = 0;
    while (true) {
        const float a = (__uint_as_float(v0.x) + __uint_as_float(v1.x)) + (__uint_as_float(v2.x) + __uint_as_float(v3.x));
        const float b = (__uint_as_float(v0.y) + __uint_as_float(v1.y)) + (__uint_as_float(v2.y) + __uint_as_float(v3.y));
        const float c = (__uint_as_float(v0.z) + __uint_as_float(v1.z)) + (__uint_as_float(v2.z) + __uint_as_float(v3.z));
        const float d = (__uint_as_float(v0.w) + __uint_as_float(v1.w)) + (__uint_as_float(v2.w) + __uint_as_float(v3.w));
        float k0 = hi ? b : a, k1 = hi ? d : c;
        k0 += __shfl_xor_sync(~0u, hi ? a : b, 4); k1 += __shfl_xor_sync(~0u, hi ? c : d, 4);
        const uint32_t t0 = tagdiff(v0, x), t1 = tagdiff(v1, x), t2 = tagdiff(v2, x), t3 = tagdiff(v3, x);
        k0 += __shfl_xor_sync(~0u, k0, 8); k1 += __shfl_xor_sync(~0u, k1, 8);
        const bool bad = __any_sync(~0u, ((t0 | t1 | t2) | t3) & 1);
        k0 += __shfl_xor_sync(~0u, k0, 16); k1 += __shfl_xor_sync(~0u, k1, 16);
        if (wr && !bad) st_relaxed32(dst, pack_bf16(k0, k1));
        if (!bad) break;
        ld_relaxed128_if(v0, src, t0 & 1); ld_relaxed128_if(v1, src + 1024, t1 & 1); ld_relaxed128_if(v2, src + 2048, t2 & 1); ld_relaxed128_if(v3, src + 3072, t3 & 1);
        if (++it > (1u << 22)) __trap();
    }
    return it;
}
template <int U0, int N>
__device__ __forceinline__ uint32_t stage_task(const char* src, uint32_t dst, uint32_t dstride) {
    uint4 v[N];
    uint32_t it = 0;
#pragma unroll
    for (int j = 0; j < N; j++) v[j] = ld_relaxed128(src + ((U0 + j) >> 2) * 16384 + ((U0 + j) & 3) * 1024);
    while (true) {
        uint32_t m = 0;
#pragma unroll
        for (int j = 0; j < N; j++) {
            sts128(dst + j * dstride, v[j]);
            v[j].x = __vimax3_u32(__vimax3_u32(v[j].x, v[j].y, v[j].z), v[j].w, 0u);
        }
#pragma unroll
        for (int j = 0; j < N; j += 2) m = __vimax3_u32(m, v[j].x, v[j + 1].x);
        if (!__any_sync(~0u, m == 0xFFFFFFFFu)) break;
#pragma unroll
        for (int j = 0; j < N; j++) {
            const bool miss = v[j].x == 0xFFFFFFFFu;
            uint32_t r[4];
            lds128(r, dst + j * dstride);
            v[j] = make_uint4(r[0], r[1], r[2], r[3]);
            ld_relaxed128_if(v[j], src + ((U0 + j) >> 2) * 16384 + ((U0 + j) & 3) * 1024, miss);
        }
        if (++it > (1u << 22)) __trap();
    }
    return it;
}
#define CNT(i, e) (e)
__device__ __forceinline__ uint32_t step_off(int s) { return (s & 1) * 8192 + (s >> 1) * 65536; }

__host__ __device__ constexpr int res_idx(int k) { return k < 4 ? k : (k < 6 ? 0 : k - 2); }
__host__ __device__ constexpr uint32_t xaddr(int c) {
    return c < 3 ? CH_MEMR + c * 4096 : c < 7 ? CH_RING + (c - 3) * 5120 : c < 11 ? CH_KX + (c - 7) * 4096 : c == 11 ? CH_RING + 20480 : CH_RING + (c - 12) * 5120;
}
__device__ __forceinline__ void tma_load_2d_mc(uint32_t dst, const CUtensorMap* tm, int c0, int c1, uint32_t bar) {
    asm volatile("cp.async.bulk.tensor.2d.shared::cluster.global.mbarrier::complete_tx::bytes.multicast::cluster [%0], [%1, {%3, %4}], [%2], %5;"
                 ::"r"(dst), "l"(tm), "r"(bar), "r"(c0), "r"(c1), "h"((uint16_t)7) : "memory");
}
__device__ __forceinline__ void bulk_load_mc(uint32_t dst, const void* src, uint32_t bytes, uint32_t bar) {
    asm volatile("cp.async.bulk.shared::cluster.global.mbarrier::complete_tx::bytes.multicast::cluster [%0], [%1], %2, [%3], %4;"
                 ::"r"(dst), "l"(src), "r"(bytes), "r"(bar), "h"((uint16_t)7) : "memory");
}
__device__ __forceinline__ void arrive_remote(uint32_t a) { asm volatile("mbarrier.arrive.shared::cluster.b64 _, [%0];" ::"r"(a) : "memory"); }
__device__ __forceinline__ bool mbar_test(uint32_t bar, uint32_t parity) {
    uint32_t ok;
    asm volatile("{.reg .pred p; mbarrier.test_wait.parity.shared::cta.b64 p, [%1], %2; selp.u32 %0, 1, 0, p;}"
                 : "=r"(ok) : "r"(bar), "r"(parity) : "memory");
    return ok;
}
__device__ __forceinline__ uint32_t movm(uint32_t x) {
    uint32_t y;
    asm volatile("movmatrix.sync.aligned.m8n8.trans.b16 %0, %1;" : "=r"(y) : "r"(x));
    return y;
}
__device__ __forceinline__ void st_async128(uint32_t a, uint4 v, uint32_t bar) {
    asm volatile("st.async.shared::cluster.mbarrier::complete_tx::bytes.v4.u32 [%0], {%1,%2,%3,%4}, [%5];"
                 ::"r"(a), "r"(v.x), "r"(v.y), "r"(v.z), "r"(v.w), "r"(bar) : "memory");
}

__global__ void __launch_bounds__(384, 1) chain_kernel(const __grid_constant__ ChainParams p) {
    extern __shared__ uint8_t smem_raw[];
    const int tid = threadIdx.x;
    const int warp = __shfl_sync(~0u, tid >> 5, 0);
    const int lane = __shfl_sync(~0u, tid & 31, tid & 31);
    uint32_t rank;
    asm volatile("mov.u32 %0, %%cluster_ctarank;" : "=r"(rank));
    rank = __shfl_sync(~0u, rank, 0);
    const int head = blockIdx.x / 3;
    const uint32_t cb = smem_u32(smem_raw) - SB;
    const int n2 = rank == 0 ? 6 : 5;
    const int b2 = rank == 0 ? 48 : (rank == 1 ? 54 : 59);
    if (tid == 0) {
        if (cb & 0xFFFFFF) __trap();
        for (int i = 0; i < 8; i++) mbar_init(cb + CH_BAR + 8 * i, 1);
        for (int i = 8; i < 12; i++) mbar_init(cb + CH_BAR + 8 * i, 8);
        for (int i = 0; i < 3; i++) { mbar_init(cb + B_XFA + 8 * i, 1); mbar_init(cb + B_E1 + 8 * i, 6); }
        mbar_init(cb + B_FREE, 3);
        asm volatile("fence.mbarrier_init.release.cluster;" ::: "memory");
    }
    asm volatile("griddepcontrol.launch_dependents;" ::: "memory");
    asm volatile("barrier.cluster.arrive.aligned; barrier.cluster.wait.aligned;" ::: "memory");
    if (warp >= 8) {
        reg_dec<40>();
        const int cta = blockIdx.x;
        const int aw = warp & 1, at = aw * 32 + lane;
        if (warp == 11 && lane == 0) {
            const CUtensorMap* tw = &p.tmW[rank];
            for (int c = 0; c < 12; c++) {
                const int st = c & 3;
                if (c >= 4) mbar_wait(cb + B_PE + 8 * st, ((c >> 2) - 1) & 1);
                mbar_expect_tx(cb + B_PF + 8 * st, 16384);
                tma_load_2d(cb + CH_RING + st * 16384, tw, head * 128, c * 64, cb + B_PF + 8 * st);
                tma_load_2d(cb + CH_RING + st * 16384 + 8192, tw, head * 128 + 64, c * 64, cb + B_PF + 8 * st);
                if (c == 3) {
                    mbar_expect_tx(cb + B_WS, 65536);
                    for (int j = 0; j < 8; j++) tma_load_2d(cb + CH_WS + j * 8192, tw, head * 128 + (j & 1) * 64, 768 + (j >> 1) * 64, cb + B_WS);
                }
            }
            mbar_expect_tx(cb + B_WO, (16 + n2) * 4096);
            for (int j = 0; j < 16 + n2; j++) {
                const int tile = j < 8 ? rank * 8 + j : (j < 16 ? 24 + rank * 8 + (j - 8) : b2 + (j - 16));
                tma_load_2d(cb + CH_WO + j * 4096, &p.tmWo, tile * 16, head * 128, cb + B_WO);
            }
        }
        if (warp == 9 && lane == 0) sts32(cb + CH_BAR + 112, probe_near(p.xmem));
        if (warp == 8) {
            if (lane == 0) {
                const uint32_t np = probe_near(p.xpart);
                st_relaxed32(&g_ptab[cta], 2 | np);
                sts32(cb + CH_BAR + 116, np);
            }
            __syncwarp();
#pragma unroll 1
            for (int j = 0; j < 3; j++) {
                uint32_t v, it = 0;
                do {
                    asm volatile("ld.relaxed.gpu.global.u32 %0, [%1];" : "=r"(v) : "l"(&g_ptab[j * 32 + lane]) : "memory");
                    if (++it > (1u << 22)) __trap();
                } while (__any_sync(~0u, v == 0));
                sts32(cb + CH_BAR + 96 + j * 4, __ballot_sync(~0u, v & 1));
            }
        }
        __syncwarp();
        bar_sync(NB_W0, 384);
        const uint32_t near = __shfl_sync(~0u, lds32(cb + CH_BAR + 112) | (lds32(cb + CH_BAR + 116) << 1), 0);
        const uint32_t a16 = at * 16;
        auto rsrc = [&](int w, uint32_t a) {
            const uint32_t o = (w * 96 + cta) * 8192;
            return p.xpart + (o + ((__popc(o & L2_HASH) ^ (near >> 1)) & 1) * 4096 + aw * 64) + (((a & 0x1C0) << 1) + (a & 48));
        };
        auto rdst = [&](int w, uint32_t so, uint32_t a) {
            const uint32_t u = (w * 96 + cta) * 64 + aw * 32;
            return p.xmem + (so + (u >> 12) * 16384 + (u & 4095)) + (((a >> 2) & 28) + ((a & 128) << 5));
        };
        auto ssrc = [&](uint32_t so, uint32_t a) { return p.xmem + (so + ((__popc(so & L2_HASH) ^ near) & 1) * 4096) + a; };
#define RTASK(w, so, tag) reduce_task(rsrc(w, opaque(a16)), rdst(w, so, opaque(a16)), tag, a16 & 64, (a16 & 256) == 0)
        if (warp < 10) {
            if (at == 0) mbar_expect_tx(cb + B_DHOP, 6144);
            bar_sync(NB_X, 320);
            bar_sync(NB_X, 320);
            {
                const uint4* m0 = (const uint4*)p.mem0 + (at & 7) * 128 + (at >> 3);
#pragma unroll 4
                for (int j = 0; j < 12; j++) sts128(cb + CH_MEMR + a16 + j * 1024, m0[j * 8]);
            }
            bar_arrive(NB_S0, 320);
            bar_arrive(NB_S1, 320);
            for (int s = 0; s < NSEG - 1; s++) {
                {
                    const uint32_t l16 = opaque(a16) + cb + aw * 512;
                    const uint32_t qp = (l16 & 0xFF000470u) + ((l16 >> 7) & 1) * 256 + ((l16 >> 8) & 1) * 128;
                    uint32_t q[2][4], kf[2][4];
                    float sc[2][4];
                    sc[0][0] = sc[0][1] = sc[0][2] = sc[0][3] = sc[1][0] = sc[1][1] = sc[1][2] = sc[1][3] = 0.f;
                    if (qp == 0x9e3779b9u) __trap();
                    mbar_wait(cb + B_DHOP, s & 1);
#pragma unroll
                    for (int i = 0; i < 2; i++) { ldsm4t(q[i], CH_QKV + i * 512 + qp); ldsm4t(kf[i], CH_QKV + 2048 + i * 512 + l16); }
#pragma unroll
                    for (int i = 0; i < 2; i++) {
                        mma16816(sc[0], q[i][0], q[i][1], q[i][2], q[i][3], kf[i][0], kf[i][1]);
                        mma16816(sc[1], q[i][0], q[i][1], q[i][2], q[i][3], kf[i][2], kf[i][3]);
                    }
                    sts64f(CH_S + 4 * 512 - aw * 1016 + l16, sc[0][0] + sc[1][2], sc[0][1] + sc[1][3]);
                    bar_arrive(NB_M0, 320);
                }
                const uint32_t so = step_off(s + 1);
                bar_sync(NB_W0, 320);
                delay(DLY_R, cb);
                TSTAMP(16);
                CNT(12, RTASK(0, so, (s & 1) ^ 1));
                TSTAMP(17);
                {
                    const uint32_t t0 = clk32();
                    if (at == 0) mbar_expect_tx(cb + B_DHOP, 6144);
                    if (s + 2 < NSEG) bar_sync(NB_X, 320);
                    while (clk32() - t0 < DLY_S) {}
                }
                const char* ss = ssrc(so, opaque(a16));
                CNT(13, (stage_task<0, 6>(ss, cb + CH_MEMR + a16, 1024)));
                bar_arrive(NB_S0, 320);
                TSTAMP(18);
                CNT(14, (stage_task<6, 6>(ss, cb + CH_MEMR + 6144 + a16, 1024)));
                bar_arrive(NB_S1, 320);
                TSTAMP(19);
            }
        } else {
            for (int s = -2; s < NSEG; s++) {
                const uint32_t so = step_off(s);
                if (s >= 1) {
                    bar_sync(NB_W1, 320);
                    delay(DLY_R, cb);
                    CNT(15, RTASK(1, so, s & 1));
                    TSTAMP(20);
                    bar_sync(NB_W2, 320);
                    if (cta < 64) RTASK(2, so, s & 1);
                    else delay(450, cb);
                    TSTAMP(21);
                }
                const uint32_t t0 = clk32();
                if (s >= -1 && s + 1 < NSEG && a16 == 0) {
                    mbar_wait(cb + B_E4, (s + 1) & 1);
                    mbar_expect_tx(cb + B_XFS, 16384);
                    tma_load_2d_mc(cb + xaddr(12) + rank * 5120, &p.tmX, (12 + rank) * 64, (s + 1) * SEG, cb + B_XFS);
                    if (rank == 0) tma_load_2d_mc(cb + xaddr(15), &p.tmX, 15 * 64, (s + 1) * SEG, cb + B_XFS);
                }
                __syncwarp();
                while (clk32() - t0 < DLY_S2) {}
                if (s >= 0) {
                    const uint32_t a = opaque(a16);
                    const uint32_t s2dst = cb + CH_RING + 4096 + ((a & 112) << 3) + (((a >> 3) ^ a) & 112);
                    if (s >= 1) stage_task<12, 4>(ssrc(so, a), s2dst, 5120);
                    else {
                        const uint4* m0 = (const uint4*)p.mem0 + ((a >> 4) & 7) * 128 + (a >> 7);
#pragma unroll
                        for (int j = 0; j < 4; j++) sts128(s2dst + j * 5120, m0[96 + j * 8]);
                    }
                }
                if (s >= -1) {
                    if (s + 1 < NSEG) {
                        if (a16 == 512) {
                            mbar_wait(cb + B_E3, (s + 1) & 1);
                            if (s >= 0) {
                                mbar_expect_tx(cb + B_KV, 16384);
                                if (rank > 0) bulk_load_mc(cb + CH_KX - 8192 + rank * 8192, (const char*)g_qkv + (size_t)((s * NH + head) * 3 + rank) * 8192, 8192, cb + B_KV);
                            }
                        }
                        __syncwarp();
                        mbar_wait(cb + B_XFS, (s + 1) & 1);
                    }
                    fence_async_smem();
                    bar_arrive(NB_S2, 320);
                    TSTAMP(22);
                }
                if (s + 4 < NSEG) {
                    if (a16 == 528 && cta < 16)
                        asm volatile("cp.async.bulk.prefetch.tensor.2d.L2.global.tile [%0, {%1, %2}];" ::"l"(&p.tmX), "r"(cta * 64), "r"((s + 4) * SEG) : "memory");
                    if (a16 >= 512 && a16 < 576 && cta < 64)
                        asm volatile("prefetch.global.L2 [%0];" ::"l"(p.xmem + step_off(s + 4) + (cta >> 4) * 16384 + (cta & 15) * 512 + (a16 - 512) * 8) : "memory");
                }
                if (s + 2 < NSEG && a16 == 0) {
                    mbar_wait(cb + B_E1, s & 1);
                    mbar_expect_tx(cb + B_XFA, 32768);
                    tma_load_2d_mc(cb + xaddr(0) + rank * 4096, &p.tmX, rank * 64, (s + 2) * SEG, cb + B_XFA);
                    tma_load_2d_mc(cb + xaddr(3) + rank * 5120, &p.tmX, (3 + rank) * 64, (s + 2) * SEG, cb + B_XFA);
                    if (rank > 0) tma_load_2d_mc(cb + xaddr(5) + rank * 5120, &p.tmX, (1 + rank * 5) * 64, (s + 2) * SEG, cb + B_XFA);
                }
                __syncwarp();
                if (s >= -1) bar_sync(NB_F, 320);
                if (s + 2 < NSEG && a16 == 0) {
                    mbar_expect_tx(cb + B_XFK, 16384);
                    arrive_remote(mapa(B_FREE, 0)); arrive_remote(mapa(B_FREE, 1)); arrive_remote(mapa(B_FREE, 2));
                    mbar_wait(cb + B_FREE, s & 1);
                    tma_load_2d_mc(cb + xaddr(7) + rank * 4096, &p.tmX, (7 + rank) * 64, (s + 2) * SEG, cb + B_XFK);
                    if (rank == 0) tma_load_2d_mc(cb + xaddr(10), &p.tmX, 10 * 64, (s + 2) * SEG, cb + B_XFK);
                }
                if (a16 == 512) {
                    asm volatile("fence.release.gpu;" ::: "memory");
                    asm volatile("fence.proxy.async.global;" ::: "memory");
                    if (s >= 0) asm volatile("red.relaxed.gpu.global.add.u32 [%0], 1;" ::"l"(&g_cnt[(C_SEG + s) * 32]) : "memory");
                }
                __syncwarp();
                TSTAMP(26);
            }
        }
    } else {
        reg_inc<232>();
        uint32_t wr[46][4];
        const uint32_t l16 = cb + lane * 16;
        {
            const int krow = (lane >> 4) * 8 + (lane & 7);
            const int ch = (warp & 3) * 2 + ((lane >> 3) & 1);
            const uint32_t off = (warp >> 2) * 8192 + krow * 128 + ((ch ^ (krow & 7)) << 4);
#pragma unroll
            for (int c = 0; c < 12; c++) {
                mbar_wait(cb + B_PF + 8 * (c & 3), (c >> 2) & 1);
#pragma unroll
                for (int k = 0; k < 4; k++) {
                    if (c != 1 || k >= 2) ldsm4t(wr[res_idx(c * 4 + k)], cb + CH_RING + (c & 3) * 16384 + off + k * 2048);
                    else {
                        uint32_t a[4];
                        lds128(a, l16 + CH_RING + 16384 + k * 8192 + warp * 512);
                        sts128(l16 + CH_W2 + k * 4096 + warp * 512, make_uint4(a[0], a[1], a[2], a[3]));
                    }
                }
                __syncwarp();
                if (lane == 0) mbar_arrive(cb + B_PE + 8 * (c & 3));
            }
            fence_async_smem();
            bar_sync(NB_W0, 384);
        }
#define XRELEASE(bar) do { const uint32_t _l = opaque(l16) & 0x1F0; if ((warp & 3) == 0 && _l < 48) arrive_remote((_l << 20) + (bar)); } while (0)
        if (mapa(B_E1, 2) != (2u << 24) + B_E1) __trap();
        XRELEASE(B_E1);
        uint32_t pinfo = (lane & 1) * 64 + (lane >> 2) * 8 + ((lane >> 1) & 1) * 8192;
#pragma unroll
        for (int i = 0; i < 6; i++) {
            const int w = i >> 1;
            const int rc = ((w < 2 ? rank * 8 : (b2 - 48)) + warp) * 4 + ((lane >> 1) & 1) + (i & 1) * 2;
            const uint32_t v = lds32(cb + CH_BAR + 96 + (rc >> 5) * 4) >> (rc & 31);
            pinfo |= ((__popc(((w * 96 + rc) * 8192) & L2_HASH) ^ v) & 1) << (16 + i);
        }
        const uint64_t da = make_desc(CH_WS, 16, 1024, 1) + (warp >> 2) * 512;
        mbar_wait(cb + B_WS, 0);
        for (int s = -1; s < NSEG; s++) {
            float xa[20];
            if (s + 1 < NSEG) {
                TSTAMP(24);
                mbar_wait(cb + B_XFA, (s + 1) & 1);
                wg_fence();
#pragma unroll
                for (int c = 0; c < 12; c++) {
                    if (c == 7) mbar_wait(cb + B_XFK, (s + 1) & 1);
                    if (c == 4 || c == 7 || c == 8) wg_fence();
#pragma unroll
                    for (int k = 0; k < 4; k++) {
                        const uint64_t dx = make_desc(xaddr(c), 16, 1024, 1) + k * 2;
                        if (c == 1 && k < 2) wgmma_ss_n32_t10(xa, make_desc(CH_W2, 16, 1024, 1) + (warp >> 2) * 256 + k * 128, dx, 1);
                        else wgmma_rs_n32_t0(xa, wr[res_idx(c * 4 + k)], dx, (c | k) != 0);
                    }
                    if (c == 2 || c == 3 || c == 6 || c == 7 || c == 10 || c == 11) wg_commit();
                    if (c == 3 || c == 7 || c == 11) {
                        wg_wait<1>();
                        if (c == 3) bar_arrive(NB_X, 320);
                        else XRELEASE(c == 7 ? B_E4 : B_E3);
                    }
                }
                wg_wait<0>();
            } else {
#pragma unroll
                for (int i = 0; i < 16; i++) xa[i] = 0.f;
            }
            TSTAMP(23);
            xa[16] = xa[17] = xa[18] = xa[19] = 0.f;
            if (s >= 0) {
                float acc[4] = {0.f, 0.f, 0.f, 0.f};
                uint32_t wc[2][4];
                {
                    const uint32_t a = opaque(l16);
                    const uint32_t w2 = cb + CH_W2 + (warp >> 2) * 4096 + ((a & 256) << 2) + ((a & 112) << 3) + ((((warp & 3) * 32 + ((a & 128) >> 3)) ^ a) & 112);
                    ldsm4t(wc[0], w2); ldsm4t(wc[1], w2 + 2048);
                }
#pragma unroll
                for (int w = 0; w < 2; w++) {
                    bar_sync(NB_S0 + w, 320);
                    uint32_t b[3][4];
#define PAIR(i) (w * 12 + (w == 0 ? ((i) == 0 ? 2 : (i) == 2 ? 0 : (i)) : (i)))
#pragma unroll
                    for (int i = 0; i < 2; i++) ldsm4(b[i], l16 + CH_MEMR + PAIR(i) * 512);
                    TSTAMPD(w, b[0][0]);
#pragma unroll
                    for (int i = 0; i < 12; i++) {
                        const int k = PAIR(i) * 2;
                        if (i + 2 < 12) ldsm4(b[(i + 2) % 3], l16 + CH_MEMR + PAIR(i + 2) * 512);
                        const uint32_t* a0 = k == 4 ? wc[0] : wr[res_idx(k)];
                        const uint32_t* a1 = k == 4 ? wc[1] : wr[res_idx(k + 1)];
                        mma16816(xa + 16, a0[0], a0[1], a0[2], a0[3], b[i % 3][0], b[i % 3][1]);
                        mma16816(acc, a1[0], a1[1], a1[2], a1[3], b[i % 3][2], b[i % 3][3]);
                    }
                }
                xa[16] += acc[0]; xa[17] += acc[1]; xa[18] += acc[2]; xa[19] += acc[3];
            }
            TSTAMP(2);
            bar_sync(NB_S2, 320);
            wg_fence();
#pragma unroll
            for (int k = 0; k < 16; k++) wgmma_ss_n40_t10(xa, da + (k >> 2) * 1024 + (k & 3) * 128, make_desc(xaddr(12 + (k >> 2)), 16, 1024, 1) + (k & 3) * 2, 1);
            wg_commit();
            const uint32_t l4w = ((opaque(l16) >> 2) & 124) + warp * 256;
            uint32_t rd[3];
#pragma unroll
            for (int r = 0; r < 3; r++) rd[r] = mapa(l4w + CH_QKV + rank * 2048, r);
            wg_wait<0>();
            TSTAMP(3);
            if (s >= 0) {
                uint32_t w0 = pack_bf16(xa[16], xa[17]), w1 = pack_bf16(xa[18], xa[19]);
                if (s < NSEG - 1) {
#pragma unroll
                    for (int r = 0; r < 3; r++) {
                        const uint32_t rb = mapa(B_DHOP, r);
                        st_async32(rd[r], w0, rb);
                        st_async32(rd[r] + 128, w1, rb);
                    }
                }
                if (rank == 1) { w0 = movm(w0); w1 = movm(w1); }
                if (rank > 0) asm volatile("st.global.L1::no_allocate.v2.u32 [%0], {%1,%2};" ::"l"((char*)g_kvmem + ((s * NH + head) * 2 + (rank - 1)) * 2048 + warp * 256 + (l4w & 124) * 2), "r"(w0), "r"(w1) : "memory");
                if (s == NSEG - 1) { bar_arrive(NB_F, 320); break; }
            }
            XRELEASE(B_E1);
            TSTAMP(4);
            {
            uint32_t xo[2][4];
#pragma unroll
            for (int i = 0; i < 8; i++) xo[i >> 2][i & 3] = pack_bf16(xa[2 * i], xa[2 * i + 1]);
            if (rank < 2) {
#pragma unroll
                for (int i = 0; i < 8; i++) xo[i >> 2][i & 3] = movm(xo[i >> 2][i & 3]);
                if (rank == 0) {
#pragma unroll
                    for (int i = 0; i < 2; i++) { const uint32_t t = xo[i][1]; xo[i][1] = xo[i][2]; xo[i][2] = t; }
                }
            }
                char* dst = (char*)g_qkv + (size_t)(((s + 1) * NH + head) * 3 + rank) * 8192 + warp * 512 + (l4w & 124) * 4;
                asm volatile("st.global.L1::no_allocate.v4.u32 [%0], {%1,%2,%3,%4};" ::"l"(dst), "r"(xo[0][0]), "r"(xo[0][1]), "r"(xo[0][2]), "r"(xo[0][3]) : "memory");
                asm volatile("st.global.L1::no_allocate.v4.u32 [%0], {%1,%2,%3,%4};" ::"l"(dst + 4096), "r"(xo[1][0]), "r"(xo[1][1]), "r"(xo[1][2]), "r"(xo[1][3]) : "memory");
            }
            if (s >= 0) {
                const uint32_t lq = opaque(l16);
                mbar_wait(cb + B_KV, s & 1);
                uint32_t kf[4][2], vf[4][4];
#pragma unroll
                for (int i = 0; i < 4; i++)
                    asm volatile("ld.shared.v2.u32 {%0,%1}, [%2];" : "=r"(kf[i][0]), "=r"(kf[i][1])
                                 : "r"(lq + CH_KX + (((warp >> 1) & 1) * 8 + (warp >> 2) * 4 + i) * 512 + (warp & 1) * 8) : "memory");
#pragma unroll
                for (int i = 0; i < 4; i++) lds128(vf[i], lq + CH_VX + ((i & 1) * 8 + (warp & 3) * 2 + (i >> 1)) * 512);
                const uint32_t qp = (lq & 0xFF000070u) + ((lq >> 7) & 1) * 256 + ((lq >> 8) & 1) * 128 + (warp >> 2) * 1024;
                mbar_wait(cb + B_DHOP, s & 1);
                TSTAMP(5);
                {
                    uint32_t q[2][4];
                    float sc[2][4];
                    sc[0][0] = sc[0][1] = sc[0][2] = sc[0][3] = sc[1][0] = sc[1][1] = sc[1][2] = sc[1][3] = 0.f;
                    ldsm4t(q[0], qp + CH_QKV);
                    ldsm4t(q[1], qp + CH_QKV + 512);
#pragma unroll
                    for (int i = 0; i < 2; i++) {
                        mma16816(sc[0], q[i][0], q[i][1], q[i][2], q[i][3], kf[2 * i][0], kf[2 * i][1]);
                        mma16816(sc[1], q[i][0], q[i][1], q[i][2], q[i][3], kf[2 * i + 1][0], kf[2 * i + 1][1]);
                    }
                    sts64f(CH_S + (warp & 3) * 512 + (warp >> 2) * 8 + lq, sc[0][0] + sc[1][2], sc[0][1] + sc[1][3]);
                }
                TSTAMP(6);
                if (warp < 4) {
                    uint32_t vm[4];
                    ldsm4(vm, lq + CH_QKV + 4096 + warp * 512);
                    bar_sync(NB_M0, 320);
                    bar_arrive(NB_F, 320);
                    float e[10];
#pragma unroll
                    for (int j = 0; j < 5; j++) {
                        float4 v;
                        asm volatile("ld.shared.v4.f32 {%0,%1,%2,%3}, [%4];" : "=f"(v.x), "=f"(v.y), "=f"(v.z), "=f"(v.w) : "r"(CH_S + j * 512 + lq) : "memory");
                        e[2 * j] = v.x + v.z; e[2 * j + 1] = v.y + v.w;
                    }
                    float m = fmaxf(fmaxf(fmaxf(e[0], e[1]), fmaxf(e[2], e[3])), fmaxf(fmaxf(e[4], e[5]), fmaxf(e[6], e[7])));
                    m = fmaxf(m, fmaxf(e[8], e[9]));
                    m = fmaxf(m, __shfl_xor_sync(~0u, m, 1));
                    m = fmaxf(m, __shfl_xor_sync(~0u, m, 2));
                    const float ms = m * SM_SCALE_LOG2;
                    uint32_t pp[5];
#pragma unroll
                    for (int j = 0; j < 5; j++) pp[j] = pack_bf16(ex2(fmaf(e[2 * j], SM_SCALE_LOG2, -ms)), ex2(fmaf(e[2 * j + 1], SM_SCALE_LOG2, -ms)));
                    float o0[4] = {0.f, 0.f, 0.f, 0.f}, o1[4] = {0.f, 0.f, 0.f, 0.f}, l[4] = {0.f, 0.f, 0.f, 0.f};
                    const uint32_t one = 0x3F803F80u;
                    mma16816(l, one, one, one, one, pp[0], pp[1]);
                    mma16816(o0, vf[0][0], vf[0][1], vf[0][2], vf[0][3], pp[0], pp[1]);
                    mma16816(o1, vf[2][0], vf[2][1], vf[2][2], vf[2][3], pp[0], pp[1]);
                    mma16816(l, one, one, one, one, pp[2], pp[3]);
                    mma16816(o0, vf[1][0], vf[1][1], vf[1][2], vf[1][3], pp[2], pp[3]);
                    mma16816(o1, vf[3][0], vf[3][1], vf[3][2], vf[3][3], pp[2], pp[3]);
                    mma1688(l, one, one, pp[4]);
                    mma1688(o0, vm[0], vm[1], pp[4]);
                    mma1688(o1, vm[2], vm[3], pp[4]);
                    sts64f(CH_L + (lq & 0xFF000030u), l[0], l[1]);
                    stsm4(lq + CH_O + warp * 512, pack_bf16(o0[0], o0[1]), pack_bf16(o0[2], o0[3]), pack_bf16(o1[0], o1[1]), pack_bf16(o1[2], o1[3]));
                    TSTAMP(7);
                } else {
                    bar_arrive(NB_M0, 320);
                    bar_arrive(NB_F, 320);
                }
                const uint32_t wo = lq + CH_WO + warp * 4096;
                uint32_t wa[4][4];
#pragma unroll
                for (int i = 0; i < 3; i++) lds128(wa[i], wo + i * 512);
                bar_sync(NB_M1, 256);
                uint32_t ob[4][4];
#pragma unroll
                for (int i = 0; i < 4; i++) ldsm4t(ob[i], lq + CH_O + i * 512);
                TSTAMPD(8, ob[0][0]);
                const uint32_t tag = (s & 1) ^ 1;
#pragma unroll
                for (int w = 0; w < 3; w++) {
                    if (w < 2 || warp < n2) {
                        float c[4] = {0.f, 0.f, 0.f, 0.f}, c2[4] = {0.f, 0.f, 0.f, 0.f};
#pragma unroll
                        for (int i = 0; i < 8; i++) {
                            const int nx = w * 8 + i + 3;
                            if (nx < 24) lds128(wa[nx & 3], wo + (nx >> 3) * 32768 + (nx & 7) * 512);
                            const int cu = (w * 8 + i) & 3;
                            mma16816((i & 1) ? c2 : c, wa[cu][0], wa[cu][1], wa[cu][2], wa[cu][3], ob[i >> 1][(i & 1) * 2], ob[i >> 1][(i & 1) * 2 + 1]);
                        }
                        c[0] += c2[0]; c[1] += c2[1]; c[2] += c2[2]; c[3] += c2[3];
                        float ra, rb;
                        lds64f(CH_L + (lq & 0xFF000030u), ra, rb);
                        asm("rcp.approx.ftz.f32 %0, %0;" : "+f"(ra));
                        asm("rcp.approx.ftz.f32 %0, %0;" : "+f"(rb));
                        const uint32_t pi = opaque(pinfo);
                        char* dst = p.xpart + (size_t)((w < 2 ? w * 24 + rank * 8 : b2) + warp) * 32768 + head * 128;
                        st_relaxed64(dst + ((pi & 0xFFFF) | ((pi >> (4 + 2 * w)) & 4096)), (__float_as_uint(c[0] * ra) & ~1u) | tag, (__float_as_uint(c[1] * rb) & ~1u) | tag);
                        st_relaxed64(dst + 16384 + ((pi & 0xFFFF) | ((pi >> (5 + 2 * w)) & 4096)), (__float_as_uint(c[2] * ra) & ~1u) | tag, (__float_as_uint(c[3] * rb) & ~1u) | tag);
                    }
                    bar_arrive(NB_W0 + w, 320);
                    TSTAMP(9 + w);
                }
            } else {
                bar_arrive(NB_F, 320);
                mbar_wait(cb + B_WO, 0);
                const int ln = (opaque(l16) >> 4) & 31;
                const int krow = (ln >> 4) * 8 + (ln & 7);
                const uint32_t wa = cb + CH_WO + warp * 4096 + krow * 32 + ((((ln >> 3) & 1) ^ ((krow >> 2) & 1)) << 4);
#pragma unroll 1
                for (int i = 0; i < (warp < n2 ? 24 : 16); i++) {
                    uint32_t a[4];
                    const uint32_t o = (i >> 3) * 32768 + (i & 7) * 512;
                    ldsm4t(a, wa + o);
                    __syncwarp();
                    sts128(l16 + CH_WO + warp * 4096 + o, make_uint4(a[0], a[1], a[2], a[3]));
                }
                __syncwarp();
            }
        }
    }
    asm volatile("barrier.cluster.arrive.aligned; barrier.cluster.wait.aligned;" ::: "memory");
}

typedef CUresult (*EncodeFn)(CUtensorMap*, CUtensorMapDataType, cuuint32_t, void*, const cuuint64_t*, const cuuint64_t*,
                             const cuuint32_t*, const cuuint32_t*, CUtensorMapInterleave, CUtensorMapSwizzle,
                             CUtensorMapL2promotion, CUtensorMapFloatOOBfill);
static EncodeFn g_encode = nullptr;

static void make_map(CUtensorMap* tm, const void* ptr, uint64_t cols, uint64_t rows, uint32_t bc, uint32_t br, CUtensorMapSwizzle sw) {
    cuuint64_t dims[2] = {cols, rows};
    cuuint64_t strides[1] = {cols * 2};
    cuuint32_t box[2] = {bc, br};
    cuuint32_t es[2] = {1, 1};
    g_encode(tm, CU_TENSOR_MAP_DATA_TYPE_BFLOAT16, 2, (void*)ptr, dims, strides, box, es, CU_TENSOR_MAP_INTERLEAVE_NONE, sw,
             CU_TENSOR_MAP_L2_PROMOTION_L2_256B, CU_TENSOR_MAP_FLOAT_OOB_FILL_NONE);
}

extern "C" void kernel_launch(void* const* d_in, const int* in_sizes, int n_in, void* d_out, int out_size) {
    const bf16* x = (const bf16*)d_in[0];
    const bf16* mem0 = (const bf16*)d_in[1];
    const bf16* Wq = (const bf16*)d_in[2];
    const bf16* Wk = (const bf16*)d_in[3];
    const bf16* Wv = (const bf16*)d_in[4];
    const bf16* Wo = (const bf16*)d_in[5];
    const bf16* w1 = (const bf16*)d_in[8];
    const bf16* b1 = (const bf16*)d_in[9];
    const bf16* w2 = (const bf16*)d_in[10];
    const bf16* b2 = (const bf16*)d_in[11];
    const bf16* gw = (const bf16*)d_in[12];
    if (!g_encode) {
        void* fn = nullptr;
        cudaDriverEntryPointQueryResult st;
        cudaGetDriverEntryPoint("cuTensorMapEncodeTiled", &fn, cudaEnableDefault, &st);
        g_encode = (EncodeFn)fn;
        cudaFuncSetAttribute(worker_kernel, cudaFuncAttributeMaxDynamicSharedMemorySize, WK_SMEM);
        cudaFuncSetAttribute(chain_kernel, cudaFuncAttributeMaxDynamicSharedMemorySize, CH_SMEM);
    }
    void *hbuf, *bbuf, *obuf;
    cudaGetSymbolAddress(&hbuf, g_h);
    cudaGetSymbolAddress(&bbuf, g_b);
    cudaGetSymbolAddress(&obuf, g_o);
    const CUtensorMapSwizzle SW128 = CU_TENSOR_MAP_SWIZZLE_128B;
    cudaStream_t st = cudaStreamPerThread;

    void* xc;
    cudaGetSymbolAddress(&xc, g_xchg);
    char* xpage = (char*)(((uintptr_t)xc + (2u << 20) - 1) & ~(uintptr_t)((2u << 20) - 1));
    prep_kernel<<<256, 256, 0, st>>>(x, gw, (uint4*)xpage);

    ChainParams cp;
    make_map(&cp.tmW[0], Wq, HD, DM, 64, 64, SW128);
    make_map(&cp.tmW[1], Wk, HD, DM, 64, 64, SW128);
    make_map(&cp.tmW[2], Wv, HD, DM, 64, 64, SW128);
    make_map(&cp.tmWo, Wo, DM, HD, 16, 128, CU_TENSOR_MAP_SWIZZLE_32B);
    make_map(&cp.tmX, x, DM, S_TOK, 64, 32, SW128);
    cp.mem0 = mem0; cp.xmem = xpage; cp.xpart = xpage + (2u << 20);
    {
        cudaLaunchConfig_t cfg = {};
        cfg.gridDim = dim3(96); cfg.blockDim = dim3(384); cfg.dynamicSmemBytes = CH_SMEM; cfg.stream = st;
        cudaLaunchAttribute at[1];
        at[0].id = cudaLaunchAttributeClusterDimension;
        at[0].val.clusterDim.x = 3; at[0].val.clusterDim.y = 1; at[0].val.clusterDim.z = 1;
        cfg.attrs = at; cfg.numAttrs = 1;
        cudaLaunchKernelEx(&cfg, chain_kernel, cp);
    }
    WorkParams wp;
    make_map(&wp.tmA[T_FFN1], x, DM, S_TOK, 64, 128, SW128);
    make_map(&wp.tmB[T_FFN1], w1, FF, DM, 64, 64, SW128);
    make_map(&wp.tmC[T_FFN1], hbuf, FF, S_TOK, 64, 64, SW128);
    make_map(&wp.tmA[T_FFN2], hbuf, FF, S_TOK, 64, 128, SW128);
    make_map(&wp.tmB[T_FFN2], w2, DM, FF, 64, 64, SW128);
    make_map(&wp.tmC[T_FFN2], bbuf, DM, S_TOK, 64, 64, SW128);
    make_map(&wp.tmA[T_OPROJ], obuf, HD, S_TOK, 64, 128, SW128);
    make_map(&wp.tmB[T_OPROJ], Wo, DM, HD, 64, 64, SW128);
    make_map(&wp.tmC[T_OPROJ], d_out, DM, S_TOK, 64, 64, SW128);
    make_map(&wp.tmO32, obuf, HD, S_TOK, 64, 32, SW128);
    wp.bias[0] = b1; wp.bias[1] = b2;
    {
        cudaLaunchConfig_t cfg = {};
        cfg.gridDim = dim3(132); cfg.blockDim = dim3(384); cfg.dynamicSmemBytes = WK_SMEM; cfg.stream = st;
        cudaLaunchAttribute at[1];
        at[0].id = cudaLaunchAttributeProgrammaticStreamSerialization;
        at[0].val.programmaticStreamSerializationAllowed = 1;
        cfg.attrs = at; cfg.numAttrs = 1;
        cudaLaunchKernelEx(&cfg, worker_kernel, wp);
    }
}
```

```cpp
#include <cuda_runtime.h>
#include <cuda_bf16.h>
#include <cuda.h>
#include <stdint.h>

typedef __nv_bfloat16 bf16;

constexpr int S_TOK = 2048, DM = 1024, NH = 32, DH = 128, HD = 4096, FF = 3584;
constexpr int NSEG = 64, SEG = 32;

__device__ __align__(1024) bf16 g_qkv[(size_t)S_TOK * 3 * HD];
__device__ __align__(1024) bf16 g_h[(size_t)S_TOK * FF];
__device__ __align__(1024) bf16 g_b[(size_t)S_TOK * DM];
__device__ __align__(1024) bf16 g_o[(size_t)S_TOK * HD];
__device__ float g_gate[S_TOK];
__device__ __align__(1024) uint32_t g_kvmem[NSEG * NH * 2 * 512];
__device__ __align__(1024) uint4 g_xchg[3 * 131072];
enum { C_F1 = 4, C_F2 = 20, C_XA = 36, C_SEG = 52, C_DONE = 116, C_PTAB = 117, C_SPLIT = 120, C_N = 136 };
__device__ __align__(128) uint32_t g_cnt[C_N * 32];
__device__ __align__(1024) float4 g_split[66 * 3 * 4096];

__device__ __forceinline__ uint32_t smem_u32(const void* p) { return (uint32_t)__cvta_generic_to_shared(p); }
__device__ __forceinline__ void mbar_init(uint32_t bar, uint32_t cnt) {
    asm volatile("mbarrier.init.shared::cta.b64 [%0], %1;" ::"r"(bar), "r"(cnt) : "memory");
}
__device__ __forceinline__ void mbar_expect_tx(uint32_t bar, uint32_t bytes) {
    asm volatile("mbarrier.arrive.expect_tx.shared::cta.b64 _, [%0], %1;" ::"r"(bar), "r"(bytes) : "memory");
}
__device__ __forceinline__ void mbar_arrive(uint32_t bar) {
    asm volatile("mbarrier.arrive.shared::cta.b64 _, [%0];" ::"r"(bar) : "memory");
}
__device__ __forceinline__ bool mbar_try(uint32_t bar, uint32_t parity) {
    uint32_t ok;
    asm volatile("{.reg .pred p; mbarrier.try_wait.parity.shared::cta.b64 p, [%1], %2; selp.u32 %0, 1, 0, p;}"
                 : "=r"(ok) : "r"(bar), "r"(parity) : "memory");
    return ok;
}
__device__ __forceinline__ void mbar_wait(uint32_t bar, uint32_t parity) {
    if (mbar_try(bar, parity)) return;
#pragma unroll 1
    for (uint32_t i = 0; i < (1u << 22); i++)
        if (mbar_try(bar, parity)) return;
    __trap();
}
__device__ __forceinline__ void tma_load_2d(uint32_t dst, const CUtensorMap* tm, int c0, int c1, uint32_t bar) {
    asm volatile("cp.async.bulk.tensor.2d.shared::cluster.global.mbarrier::complete_tx::bytes [%0], [%1, {%3, %4}], [%2];"
                 ::"r"(dst), "l"(tm), "r"(bar), "r"(c0), "r"(c1) : "memory");
}
__device__ __forceinline__ void tma_store_2d(const CUtensorMap* tm, int c0, int c1, uint32_t src) {
    asm volatile("cp.async.bulk.tensor.2d.global.shared::cta.bulk_group [%0, {%2, %3}], [%1];"
                 ::"l"(tm), "r"(src), "r"(c0), "r"(c1) : "memory");
}
__device__ __forceinline__ void bulk_load(uint32_t dst, const void* src, uint32_t bytes, uint32_t bar) {
    asm volatile("cp.async.bulk.shared::cluster.global.mbarrier::complete_tx::bytes [%0], [%1], %2, [%3];"
                 ::"r"(dst), "l"(src), "r"(bytes), "r"(bar) : "memory");
}
__device__ __forceinline__ void bulk_store(void* dst, uint32_t src, uint32_t bytes) {
    asm volatile("cp.async.bulk.global.shared::cta.bulk_group [%0], [%1], %2;" ::"l"(dst), "r"(src), "r"(bytes) : "memory");
}
__device__ __forceinline__ void bulk_commit() { asm volatile("cp.async.bulk.commit_group;" ::: "memory"); }
__device__ __forceinline__ void bulk_wait_read0() { asm volatile("cp.async.bulk.wait_group.read 0;" ::: "memory"); }
__device__ __forceinline__ void bulk_wait0() { asm volatile("cp.async.bulk.wait_group 0;" ::: "memory"); }
__device__ __forceinline__ void fence_async_smem() { asm volatile("fence.proxy.async.shared::cta;" ::: "memory"); }
__device__ __forceinline__ void bar_sync(int id, int n) { asm volatile("bar.sync %0, %1;" ::"r"(id), "r"(n) : "memory"); }
__device__ __forceinline__ void bar_arrive(int id, int n) { asm volatile("bar.arrive %0, %1;" ::"r"(id), "r"(n) : "memory"); }
__device__ __forceinline__ void wg_fence() { asm volatile("wgmma.fence.sync.aligned;" ::: "memory"); }
__device__ __forceinline__ void wg_commit() { asm volatile("wgmma.commit_group.sync.aligned;" ::: "memory"); }
template <int N> __device__ __forceinline__ void wg_wait() { asm volatile("wgmma.wait_group.sync.aligned %0;" ::"n"(N) : "memory"); }
template <int N> __device__ __forceinline__ void reg_inc() { asm volatile("setmaxnreg.inc.sync.aligned.u32 %0;" ::"n"(N)); }
template <int N> __device__ __forceinline__ void reg_dec() { asm volatile("setmaxnreg.dec.sync.aligned.u32 %0;" ::"n"(N)); }
__device__ __forceinline__ uint64_t make_desc(uint32_t saddr, uint32_t lbo, uint32_t sbo, uint32_t swz) {
    return (uint64_t)((saddr & 0x3FFFF) >> 4) | ((uint64_t)(lbo >> 4) << 16) | ((uint64_t)(sbo >> 4) << 32) | ((uint64_t)swz << 62);
}
__device__ __forceinline__ uint32_t pack_bf16(float lo, float hi) {
    uint32_t r;
    asm("cvt.rn.bf16x2.f32 %0, %1, %2;" : "=r"(r) : "f"(hi), "f"(lo));
    return r;
}
__device__ __forceinline__ float bf_lo(uint32_t v) { return __uint_as_float(v << 16); }
__device__ __forceinline__ float bf_hi(uint32_t v) { return __uint_as_float(v & 0xFFFF0000u); }
__device__ __forceinline__ void ldsm4(uint32_t* r, uint32_t a) {
    asm volatile("ldmatrix.sync.aligned.m8n8.x4.shared.b16 {%0,%1,%2,%3}, [%4];"
                 : "=r"(r[0]), "=r"(r[1]), "=r"(r[2]), "=r"(r[3]) : "r"(a) : "memory");
}
__device__ __forceinline__ void ldsm4t(uint32_t* r, uint32_t a) {
    asm volatile("ldmatrix.sync.aligned.m8n8.x4.trans.shared.b16 {%0,%1,%2,%3}, [%4];"
                 : "=r"(r[0]), "=r"(r[1]), "=r"(r[2]), "=r"(r[3]) : "r"(a) : "memory");
}
__device__ __forceinline__ void stsm4(uint32_t a, uint32_t r0, uint32_t r1, uint32_t r2, uint32_t r3) {
    asm volatile("stmatrix.sync.aligned.m8n8.x4.shared.b16 [%0], {%1,%2,%3,%4};"
                 ::"r"(a), "r"(r0), "r"(r1), "r"(r2), "r"(r3) : "memory");
}
__device__ __forceinline__ void mma16816(float* d, uint32_t a0, uint32_t a1, uint32_t a2, uint32_t a3, uint32_t b0, uint32_t b1) {
    asm volatile("mma.sync.aligned.m16n8k16.row.col.f32.bf16.bf16.f32 {%0,%1,%2,%3}, {%4,%5,%6,%7}, {%8,%9}, {%0,%1,%2,%3};"
                 : "+f"(d[0]), "+f"(d[1]), "+f"(d[2]), "+f"(d[3])
                 : "r"(a0), "r"(a1), "r"(a2), "r"(a3), "r"(b0), "r"(b1));
}
__device__ __forceinline__ void mma1688(float* d, uint32_t a0, uint32_t a1, uint32_t b0) {
    asm volatile("mma.sync.aligned.m16n8k8.row.col.f32.bf16.bf16.f32 {%0,%1,%2,%3}, {%4,%5}, {%6}, {%0,%1,%2,%3};"
                 : "+f"(d[0]), "+f"(d[1]), "+f"(d[2]), "+f"(d[3])
                 : "r"(a0), "r"(a1), "r"(b0));
}
__device__ __forceinline__ uint4 ld_relaxed128(const void* p) {
    uint4 v;
    asm volatile("ld.relaxed.gpu.global.v4.u32 {%0,%1,%2,%3}, [%4];" : "=r"(v.x), "=r"(v.y), "=r"(v.z), "=r"(v.w) : "l"(p) : "memory");
    return v;
}
__device__ __forceinline__ void st_relaxed64(void* p, uint32_t a, uint32_t b) {
    asm volatile("{.reg .b64 v; mov.b64 v, {%1,%2}; st.relaxed.gpu.global.b64 [%0], v;}" ::"l"(p), "r"(a), "r"(b) : "memory");
}
__device__ __forceinline__ void st_relaxed32(void* p, uint32_t a) {
    asm volatile("st.relaxed.gpu.global.u32 [%0], %1;" ::"l"(p), "r"(a) : "memory");
}
__device__ __forceinline__ void sts128(uint32_t a, uint4 v) {
    asm volatile("st.shared.v4.u32 [%0], {%1,%2,%3,%4};" ::"r"(a), "r"(v.x), "r"(v.y), "r"(v.z), "r"(v.w) : "memory");
}
__device__ __forceinline__ void sts32(uint32_t a, uint32_t v) { asm volatile("st.shared.u32 [%0], %1;" ::"r"(a), "r"(v) : "memory"); }
__device__ __forceinline__ void sts64f(uint32_t a, float x, float y) { asm volatile("st.shared.v2.f32 [%0], {%1,%2};" ::"r"(a), "f"(x), "f"(y) : "memory"); }
__device__ __forceinline__ uint32_t lds32(uint32_t a) { uint32_t v; asm volatile("ld.shared.u32 %0, [%1];" : "=r"(v) : "r"(a) : "memory"); return v; }
__device__ __forceinline__ void lds64f(uint32_t a, float& x, float& y) { asm volatile("ld.shared.v2.f32 {%0,%1}, [%2];" : "=f"(x), "=f"(y) : "r"(a) : "memory"); }
__device__ __forceinline__ uint32_t mapa(uint32_t a, uint32_t r) { uint32_t d; asm volatile("mapa.shared::cluster.u32 %0, %1, %2;" : "=r"(d) : "r"(a), "r"(r)); return d; }
__device__ __forceinline__ void st_async32(uint32_t a, uint32_t v, uint32_t bar) {
    asm volatile("st.async.shared::cluster.mbarrier::complete_tx::bytes.u32 [%0], %1, [%2];" ::"r"(a), "r"(v), "r"(bar) : "memory");
}
__device__ __forceinline__ float ex2(float x) { float y; asm("ex2.approx.ftz.f32 %0, %1;" : "=f"(y) : "f"(x)); return y; }
__device__ __forceinline__ uint32_t clk32() { unsigned long long t; asm volatile("mov.u64 %0, %%clock64;" : "=l"(t)::"memory"); return (uint32_t)t; }

__device__ __forceinline__ void wgmma_ss_n256_t01(float* d, uint64_t da, uint64_t db, int scale_d) {
    asm volatile("{.reg .pred p; setp.ne.b32 p, %130, 0;\n"
        "wgmma.mma_async.sync.aligned.m64n256k16.f32.bf16.bf16 {%0,%1,%2,%3,%4,%5,%6,%7,%8,%9,%10,%11,%12,%13,%14,%15,%16,%17,%18,%19,%20,%21,%22,%23,%24,%25,%26,%27,%28,%29,%30,%31,%32,%33,%34,%35,%36,%37,%38,%39,%40,%41,%42,%43,%44,%45,%46,%47,%48,%49,%50,%51,%52,%53,%54,%55,%56,%57,%58,%59,%60,%61,%62,%63,%64,%65,%66,%67,%68,%69,%70,%71,%72,%73,%74,%75,%76,%77,%78,%79,%80,%81,%82,%83,%84,%85,%86,%87,%88,%89,%90,%91,%92,%93,%94,%95,%96,%97,%98,%99,%100,%101,%102,%103,%104,%105,%106,%107,%108,%109,%110,%111,%112,%113,%114,%115,%116,%117,%118,%119,%120,%121,%122,%123,%124,%125,%126,%127}, %128, %129, p, 1, 1, 0, 1;}"
        : "+f"(d[0]), "+f"(d[1]), "+f"(d[2]), "+f"(d[3]), "+f"(d[4]), "+f"(d[5]), "+f"(d[6]), "+f"(d[7]), "+f"(d[8]), "+f"(d[9]), "+f"(d[10]), "+f"(d[11]), "+f"(d[12]), "+f"(d[13]), "+f"(d[14]), "+f"(d[15]), "+f"(d[16]), "+f"(d[17]), "+f"(d[18]), "+f"(d[19]), "+f"(d[20]), "+f"(d[21]), "+f"(d[22]), "+f"(d[23]), "+f"(d[24]), "+f"(d[25]), "+f"(d[26]), "+f"(d[27]), "+f"(d[28]), "+f"(d[29]), "+f"(d[30]), "+f"(d[31]), "+f"(d[32]), "+f"(d[33]), "+f"(d[34]), "+f"(d[35]), "+f"(d[36]), "+f"(d[37]), "+f"(d[38]), "+f"(d[39]), "+f"(d[40]), "+f"(d[41]), "+f"(d[42]), "+f"(d[43]), "+f"(d[44]), "+f"(d[45]), "+f"(d[46]), "+f"(d[47]), "+f"(d[48]), "+f"(d[49]), "+f"(d[50]), "+f"(d[51]), "+f"(d[52]), "+f"(d[53]), "+f"(d[54]), "+f"(d[55]), "+f"(d[56]), "+f"(d[57]), "+f"(d[58]), "+f"(d[59]), "+f"(d[60]), "+f"(d[61]), "+f"(d[62]), "+f"(d[63]), "+f"(d[64]), "+f"(d[65]), "+f"(d[66]), "+f"(d[67]), "+f"(d[68]), "+f"(d[69]), "+f"(d[70]), "+f"(d[71]), "+f"(d[72]), "+f"(d[73]), "+f"(d[74]), "+f"(d[75]), "+f"(d[76]), "+f"(d[77]), "+f"(d[78]), "+f"(d[79]), "+f"(d[80]), "+f"(d[81]), "+f"(d[82]), "+f"(d[83]), "+f"(d[84]), "+f"(d[85]), "+f"(d[86]), "+f"(d[87]), "+f"(d[88]), "+f"(d[89]), "+f"(d[90]), "+f"(d[91]), "+f"(d[92]), "+f"(d[93]), "+f"(d[94]), "+f"(d[95]), "+f"(d[96]), "+f"(d[97]), "+f"(d[98]), "+f"(d[99]), "+f"(d[100]), "+f"(d[101]), "+f"(d[102]), "+f"(d[103]), "+f"(d[104]), "+f"(d[105]), "+f"(d[106]), "+f"(d[107]), "+f"(d[108]), "+f"(d[109]), "+f"(d[110]), "+f"(d[111]), "+f"(d[112]), "+f"(d[113]), "+f"(d[114]), "+f"(d[115]), "+f"(d[116]), "+f"(d[117]), "+f"(d[118]), "+f"(d[119]), "+f"(d[120]), "+f"(d[121]), "+f"(d[122]), "+f"(d[123]), "+f"(d[124]), "+f"(d[125]), "+f"(d[126]), "+f"(d[127])
        : "l"(da), "l"(db), "r"(scale_d));
}
__device__ __forceinline__ void wgmma_ss_n128_t01(float* d, uint64_t da, uint64_t db, int scale_d) {
    asm volatile("{.reg .pred p; setp.ne.b32 p, %66, 0;\n"
        "wgmma.mma_async.sync.aligned.m64n128k16.f32.bf16.bf16 {%0,%1,%2,%3,%4,%5,%6,%7,%8,%9,%10,%11,%12,%13,%14,%15,%16,%17,%18,%19,%20,%21,%22,%23,%24,%25,%26,%27,%28,%29,%30,%31,%32,%33,%34,%35,%36,%37,%38,%39,%40,%41,%42,%43,%44,%45,%46,%47,%48,%49,%50,%51,%52,%53,%54,%55,%56,%57,%58,%59,%60,%61,%62,%63}, %64, %65, p, 1, 1, 0, 1;}"
        : "+f"(d[0]), "+f"(d[1]), "+f"(d[2]), "+f"(d[3]), "+f"(d[4]), "+f"(d[5]), "+f"(d[6]), "+f"(d[7]), "+f"(d[8]), "+f"(d[9]), "+f"(d[10]), "+f"(d[11]), "+f"(d[12]), "+f"(d[13]), "+f"(d[14]), "+f"(d[15]), "+f"(d[16]), "+f"(d[17]), "+f"(d[18]), "+f"(d[19]), "+f"(d[20]), "+f"(d[21]), "+f"(d[22]), "+f"(d[23]), "+f"(d[24]), "+f"(d[25]), "+f"(d[26]), "+f"(d[27]), "+f"(d[28]), "+f"(d[29]), "+f"(d[30]), "+f"(d[31]), "+f"(d[32]), "+f"(d[33]), "+f"(d[34]), "+f"(d[35]), "+f"(d[36]), "+f"(d[37]), "+f"(d[38]), "+f"(d[39]), "+f"(d[40]), "+f"(d[41]), "+f"(d[42]), "+f"(d[43]), "+f"(d[44]), "+f"(d[45]), "+f"(d[46]), "+f"(d[47]), "+f"(d[48]), "+f"(d[49]), "+f"(d[50]), "+f"(d[51]), "+f"(d[52]), "+f"(d[53]), "+f"(d[54]), "+f"(d[55]), "+f"(d[56]), "+f"(d[57]), "+f"(d[58]), "+f"(d[59]), "+f"(d[60]), "+f"(d[61]), "+f"(d[62]), "+f"(d[63])
        : "l"(da), "l"(db), "r"(scale_d));
}
__device__ __forceinline__ void wgmma_ss_n32_t10(float* d, uint64_t da, uint64_t db, int scale_d) {
    asm volatile("{.reg .pred p; setp.ne.b32 p, %18, 0;\n"
        "wgmma.mma_async.sync.aligned.m64n32k16.f32.bf16.bf16 {%0,%1,%2,%3,%4,%5,%6,%7,%8,%9,%10,%11,%12,%13,%14,%15}, %16, %17, p, 1, 1, 1, 0;}"
        : "+f"(d[0]), "+f"(d[1]), "+f"(d[2]), "+f"(d[3]), "+f"(d[4]), "+f"(d[5]), "+f"(d[6]), "+f"(d[7]), "+f"(d[8]), "+f"(d[9]), "+f"(d[10]), "+f"(d[11]), "+f"(d[12]), "+f"(d[13]), "+f"(d[14]), "+f"(d[15])
        : "l"(da), "l"(db), "r"(scale_d));
}
__device__ __forceinline__ void wgmma_ss_n40_t10(float* d, uint64_t da, uint64_t db, int scale_d) {
    asm volatile("{.reg .pred p; setp.ne.b32 p, %22, 0;\n"
        "wgmma.mma_async.sync.aligned.m64n40k16.f32.bf16.bf16 {%0,%1,%2,%3,%4,%5,%6,%7,%8,%9,%10,%11,%12,%13,%14,%15,%16,%17,%18,%19}, %20, %21, p, 1, 1, 1, 0;}"
        : "+f"(d[0]), "+f"(d[1]), "+f"(d[2]), "+f"(d[3]), "+f"(d[4]), "+f"(d[5]), "+f"(d[6]), "+f"(d[7]), "+f"(d[8]), "+f"(d[9]), "+f"(d[10]), "+f"(d[11]), "+f"(d[12]), "+f"(d[13]), "+f"(d[14]), "+f"(d[15]), "+f"(d[16]), "+f"(d[17]), "+f"(d[18]), "+f"(d[19])
        : "l"(da), "l"(db), "r"(scale_d));
}
__device__ __forceinline__ void wgmma_rs_n32_t0(float* d, const uint32_t* a, uint64_t db, int scale_d) {
    asm volatile("{.reg .pred p; setp.ne.b32 p, %21, 0;\n"
        "wgmma.mma_async.sync.aligned.m64n32k16.f32.bf16.bf16 {%0,%1,%2,%3,%4,%5,%6,%7,%8,%9,%10,%11,%12,%13,%14,%15}, {%16,%17,%18,%19}, %20, p, 1, 1, 0;}"
        : "+f"(d[0]), "+f"(d[1]), "+f"(d[2]), "+f"(d[3]), "+f"(d[4]), "+f"(d[5]), "+f"(d[6]), "+f"(d[7]), "+f"(d[8]), "+f"(d[9]), "+f"(d[10]), "+f"(d[11]), "+f"(d[12]), "+f"(d[13]), "+f"(d[14]), "+f"(d[15])
        : "r"(a[0]), "r"(a[1]), "r"(a[2]), "r"(a[3]), "l"(db), "r"(scale_d));
}

constexpr float SM_SCALE_LOG2 = 0.08838834764831845f * 1.4426950408889634f;
__device__ __forceinline__ void stsm4t(uint32_t a, uint32_t r0, uint32_t r1, uint32_t r2, uint32_t r3) {
    asm volatile("stmatrix.sync.aligned.m8n8.x4.trans.shared.b16 [%0], {%1,%2,%3,%4};"
                 ::"r"(a), "r"(r0), "r"(r1), "r"(r2), "r"(r3) : "memory");
}
template <int MT>
__device__ __forceinline__ void xattn_warp(uint32_t S, uint32_t empty_bar, int seg, int head, int lane, uint32_t so, const CUtensorMap* tmO) {
    constexpr int NT = MT * 2 + 3;
    const uint32_t ln = S + lane * 16, lp = S + (lane & 7) * 16 + ((lane >> 3) & 1) * 256 + (lane >> 4) * 128;
    float sc[NT][4];
#pragma unroll
    for (int j = 0; j < NT; j++) sc[j][0] = sc[j][1] = sc[j][2] = sc[j][3] = 0.f;
    uint32_t m[4];
#pragma unroll
    for (int k = 0; k < 8; k++) {
        uint32_t a[4], b[4];
        ldsm4t(a, lp + (MT * 8 + k) * 512);
        if ((k & 1) == 0) ldsm4t(m, lp + 24576 + (k >> 1) * 512);
#pragma unroll
        for (int i = 0; i <= MT; i++) {
            ldsm4t(b, ln + 8192 + (i * 8 + k) * 512);
            mma16816(sc[2 * i], a[0], a[1], a[2], a[3], b[0], b[1]);
            mma16816(sc[2 * i + 1], a[0], a[1], a[2], a[3], b[2], b[3]);
        }
        mma16816(sc[NT - 1], a[0], a[1], a[2], a[3], m[(k & 1) * 2], m[(k & 1) * 2 + 1]);
    }
    const int g = lane >> 2, t2 = (lane & 3) * 2;
    if (t2 > g) { sc[2 * MT][0] = -INFINITY; sc[2 * MT + 1][2] = -INFINITY; }
    if (t2 + 1 > g) { sc[2 * MT][1] = -INFINITY; sc[2 * MT + 1][3] = -INFINITY; }
    sc[2 * MT + 1][0] = sc[2 * MT + 1][1] = -INFINITY;
    uint32_t pr[2][NT];
#pragma unroll
    for (int h = 0; h < 2; h++) {
        float mx = -INFINITY;
#pragma unroll
        for (int j = 0; j < NT; j++) mx = fmaxf(mx, fmaxf(sc[j][2 * h], sc[j][2 * h + 1]));
        mx = fmaxf(mx, __shfl_xor_sync(~0u, mx, 1));
        mx = fmaxf(mx, __shfl_xor_sync(~0u, mx, 2));
        float l = 0.f;
#pragma unroll
        for (int j = 0; j < NT; j++) {
            sc[j][2 * h] = ex2((sc[j][2 * h] - mx) * SM_SCALE_LOG2); sc[j][2 * h + 1] = ex2((sc[j][2 * h + 1] - mx) * SM_SCALE_LOG2);
            l += sc[j][2 * h] + sc[j][2 * h + 1];
        }
        l += __shfl_xor_sync(~0u, l, 1);
        l += __shfl_xor_sync(~0u, l, 2);
        l = 1.f / l;
#pragma unroll
        for (int j = 0; j < NT; j++) pr[h][j] = pack_bf16(sc[j][2 * h] * l, sc[j][2 * h + 1] * l);
    }
    uint32_t o[8][4];
#pragma unroll
    for (int w = 0; w < 8; w++) {
        float c[2][4];
        c[0][0] = c[0][1] = c[0][2] = c[0][3] = c[1][0] = c[1][1] = c[1][2] = c[1][3] = 0.f;
        if ((w & 1) == 0) ldsm4(m, ln + 26624 + (w >> 1) * 512);
#pragma unroll
        for (int i = 0; i <= MT; i++) {
            uint32_t v[4];
            ldsm4(v, ln + 16384 + (i * 8 + w) * 512);
            mma16816(c[0], v[0], v[1], v[2], v[3], pr[0][2 * i], pr[0][2 * i + 1]);
            mma16816(c[1], v[0], v[1], v[2], v[3], pr[1][2 * i], pr[1][2 * i + 1]);
        }
        mma1688(c[0], m[(w & 1) * 2], m[(w & 1) * 2 + 1], pr[0][NT - 1]);
        mma1688(c[1], m[(w & 1) * 2], m[(w & 1) * 2 + 1], pr[1][NT - 1]);
        o[w][0] = pack_bf16(c[0][0], c[0][1]); o[w][1] = pack_bf16(c[0][2], c[0][3]);
        o[w][2] = pack_bf16(c[1][0], c[1][1]); o[w][3] = pack_bf16(c[1][2], c[1][3]);
    }
    __syncwarp();
    if (lane == 0) { mbar_arrive(empty_bar); bulk_wait_read0(); }
    __syncwarp();
    const int row = (lane >> 4) * 8 + (lane & 7), hb = (lane >> 3) & 1;
#pragma unroll
    for (int w = 0; w < 8; w++) stsm4t(so + (w >> 2) * 2048 + row * 128 + ((((w & 3) * 2 + hb) ^ (row & 7)) << 4), o[w][0], o[w][1], o[w][2], o[w][3]);
    fence_async_smem();
    __syncwarp();
    if (lane == 0) {
        tma_store_2d(tmO, head * 128, seg * SEG + MT * 16, so);
        tma_store_2d(tmO, head * 128 + 64, seg * SEG + MT * 16, so + 2048);
        bulk_commit();
    }
}

enum { T_FFN1 = 0, T_FFN2 = 1, T_OPROJ = 2, T_XATT = 3, T_DONE = 4, T_GATE = 5 };
struct WorkParams {
    CUtensorMap tmA[3], tmB[3], tmC[3];
    CUtensorMap tmO16;
    const bf16* bias[2];
    const bf16* x;
    const bf16* gw;
};
constexpr int WK_STAGE = 49152, WK_NST = 4;
constexpr int WK_SMEM = WK_NST * WK_STAGE + 32768 + 256 + 1024;
#define SPLIT4 48
#define WK_DELAY 0
#define SPLIT_SEG 58
constexpr int NQF = 224 + 64 + 16;

__device__ __forceinline__ uint32_t ld_acquire(const uint32_t* p) {
    uint32_t v;
    asm volatile("ld.acquire.gpu.global.u32 %0, [%1];" : "=r"(v) : "l"(p) : "memory");
    return v;
}
__device__ __forceinline__ uint32_t ld_relaxed32(const uint32_t* p) {
    uint32_t v;
    asm volatile("ld.relaxed.gpu.global.u32 %0, [%1];" : "=r"(v) : "l"(p) : "memory");
    return v;
}
__device__ __forceinline__ void signal_cnt(int c) {
    asm volatile("red.release.gpu.global.add.u32 [%0], 1;" ::"l"(&g_cnt[c * 32]) : "memory");
}
__device__ __forceinline__ uint32_t ffn_task(int f) {
    if (f < 42) return T_FFN1 | ((f / 14) << 8) | ((f % 14) << 16);
    f -= 42;
    if (f < 16) return T_GATE | (f << 8);
    f -= 16;
    if (f < 13 * 18) {
        const int g = f / 18, r = f % 18;
        return r < 14 ? (T_FFN1 | ((g + 3) << 8) | (r << 16)) : (T_FFN2 | (g << 8) | ((r - 14) << 16));
    }
    f -= 13 * 18;
    return T_FFN2 | ((13 + (f >> 2)) << 8) | ((f & 3) << 16);
}
__device__ __forceinline__ void wait_cnt(int c, uint32_t v) {
    uint32_t n = 0;
    while (ld_acquire(&g_cnt[c * 32]) != v) { __nanosleep(64); if (++n > (1u << 24)) __trap(); }
}
__device__ __forceinline__ uint32_t pick_task(bool& ffn_left, bool first) {
    for (uint32_t it = 0; it < (1u << 24); it++) {
        uint32_t x = 0, o = 0, step = 0;
        bool late = false;
        if (!first) {
            const uint4 q = ld_relaxed128(g_cnt);
            const uint32_t last = ld_relaxed32(&g_cnt[(C_SEG + NSEG - 1) * 32]);
            late = ld_relaxed32(&g_cnt[(C_SEG + SPLIT_SEG) * 32]) == 96;
            x = q.y; o = q.z; step = q.w;
            if (q.x >= NQF) ffn_left = false;
            if (x < 256) {
                bool got = false;
                if (last == 96) { x = atomicAdd(&g_cnt[1], 1); got = x < 256; }
                else if (ld_relaxed32(&g_cnt[(C_SEG + (x >> 2)) * 32]) == 96) {
                    const uint32_t lim = (x | 3) + 1;
                    while (x < lim && !got) { const uint32_t r = atomicCAS(&g_cnt[1], x, x + 1); got = r == x; x = r; }
                }
                if (got) {
                    asm volatile("fence.acquire.gpu;" ::: "memory");
                    return T_XATT | ((x >> 2) << 8) | ((x & 3) << 16);
                }
            }
        }
        if (ffn_left) {
            const uint32_t f = atomicAdd(&g_cnt[0], 1);
            if (f < NQF) {
                const uint32_t t = ffn_task(f);
                if ((t & 255) == T_FFN2) wait_cnt(C_F1 + ((t >> 8) & 255), 28);
                return t;
            }
            ffn_left = false;
        }
        if (first) { first = false; continue; }
        if (o >= 512) return T_DONE;
        if (!late) step = 4;
        else if (step == 0) {
            const uint32_t want = o >= 512 - 4 * SPLIT4 ? 1 : (o >= 512 - 4 * 66 ? 2 : 4);
            step = atomicCAS(&g_cnt[3], 0, want);
            if (step == 0) step = want;
        }
        bool got = false;
        if (x >= 256) { o = atomicAdd(&g_cnt[2], step); got = o < 512; }
        else if ((o & (step - 1)) == 0) {
            const uint32_t c0 = ld_relaxed32(&g_cnt[(C_XA + (o >> 5)) * 32]), c1 = ld_relaxed32(&g_cnt[(C_F2 + (o >> 5)) * 32]);
            if (c0 == 128 && c1 == 16) {
                const uint32_t lim = (o | 31) + 1;
                while (o < lim && (o & (step - 1)) == 0 && !got) { const uint32_t r = atomicCAS(&g_cnt[2], o, o + step); got = r == o; o = r; }
            }
        }
        if (got) {
            uint32_t n = 0;
            while (true) {
                const uint32_t c0 = ld_relaxed32(&g_cnt[(C_XA + (o >> 5)) * 32]), c1 = ld_relaxed32(&g_cnt[(C_F2 + (o >> 5)) * 32]);
                if (c0 == 128 && c1 == 16) break;
                if (++n > (1u << 24)) __trap();
            }
            asm volatile("fence.acquire.gpu;" ::: "memory");
            return T_OPROJ | ((o >> 5) << 8) | (((o >> 2) & 7) << 16) | ((o & 3) << 24) | (step << 26);
        }
        __nanosleep(100);
    }
    __trap();
    return T_DONE;
}

template <int TYPE>
__device__ __forceinline__ void gemm_tile(const WorkParams& p, uint32_t sb, uint32_t bars, uint32_t stg, int m0, int nb, int cw, int warp, int lane,
                                          bool leader, int& st, int& ph, int& dph, int step, int& pend) {
    constexpr int BN = TYPE == T_OPROJ ? 128 : 256;
    const int KB = TYPE == T_FFN1 ? 16 : (TYPE == T_FFN2 ? 56 : 16 * step);
    const int n0 = nb * BN;
    float acc[BN / 2];
#pragma unroll
    for (int i = 0; i < BN / 2; i++) acc[i] = 0.f;
    if (TYPE == T_OPROJ) {
        if (lane == 0) bulk_wait_read0();
        bar_sync(1 + cw, 128);
        if (leader) {
            asm volatile("fence.proxy.async.global;" ::: "memory");
            mbar_expect_tx(bars + 64 + 8 * cw, 16384);
            tma_load_2d(stg, &p.tmC[T_FFN2], n0, m0 + cw * 64, bars + 64 + 8 * cw);
            tma_load_2d(stg + 8192, &p.tmC[T_FFN2], n0 + 64, m0 + cw * 64, bars + 64 + 8 * cw);
        }
    }
    int prev = 0;
    for (int kb = 0; kb < KB; kb++) {
        mbar_wait(bars + 8 * st, ph);
        const uint32_t a = sb + st * WK_STAGE;
        const uint64_t da = make_desc(a + cw * 8192, 16, 1024, 1);
        const uint64_t db = make_desc(a + 16384, 8192, 1024, 1);
        wg_fence();
#pragma unroll
        for (int k = 0; k < 4; k++) {
            if (BN == 256) wgmma_ss_n256_t01(acc, da + k * 2, db + k * 128, (kb | k) != 0);
            else wgmma_ss_n128_t01(acc, da + k * 2, db + k * 128, (kb | k) != 0);
        }
        wg_commit();
        if (kb == 2) {
            if (pend >= 0) { bulk_wait0(); signal_cnt(pend); pend = -1; }
            __syncwarp();
        }
        if (kb > 0) { wg_wait<1>(); if (leader) mbar_arrive(bars + 32 + 8 * prev); }
        prev = st;
        if (++st == WK_NST) { st = 0; ph ^= 1; }
    }
    wg_wait<0>();
    if (leader) mbar_arrive(bars + 32 + 8 * prev);
    const int g = lane >> 2, t = lane & 3;
    const int srow = warp * 16 + ((lane >> 3) & 1) * 8 + (lane & 7);
    float g0 = 0.f, g1 = 0.f;
    if (TYPE == T_OPROJ) {
        g0 = __ldcg(&g_gate[m0 + cw * 64 + warp * 16 + g]);
        g1 = __ldcg(&g_gate[m0 + cw * 64 + warp * 16 + g + 8]);
        mbar_wait(bars + 64 + 8 * cw, dph);
        dph ^= 1;
        if (step < 4) {
            const int tile = (m0 >> 4) + nb, nparts = 4 / step;
            uint32_t* cnt = &g_cnt[C_SPLIT * 32 + tile * 4 + cw * 2];
            if (leader) sts32(bars + 120 + 4 * cw, atomicAdd(cnt, 1));
            bar_sync(1 + cw, 128);
            const int ticket = lds32(bars + 120 + 4 * cw);
            float4* part = g_split + (size_t)(127 - tile) * 3 * 4096 + cw * 2048 + warp * 32 + lane;
            if (ticket < nparts - 1) {
#pragma unroll
                for (int i = 0; i < BN / 8; i++) __stcg(part + ticket * 4096 + i * 128, make_float4(acc[4 * i], acc[4 * i + 1], acc[4 * i + 2], acc[4 * i + 3]));
                bar_sync(1 + cw, 128);
                if (leader) asm volatile("red.release.gpu.global.add.u32 [%0], 1;" ::"l"(cnt + 1) : "memory");
                return;
            }
            if (leader) {
                uint32_t n = 0;
                while (ld_acquire(cnt + 1) != nparts - 1) { if (++n > (1u << 24)) __trap(); }
            }
            bar_sync(1 + cw, 128);
            for (int j = 0; j < nparts - 1; j++) {
#pragma unroll
                for (int i = 0; i < BN / 8; i++) {
                    const float4 v = __ldcg(part + j * 4096 + i * 128);
                    acc[4 * i] += v.x; acc[4 * i + 1] += v.y; acc[4 * i + 2] += v.z; acc[4 * i + 3] += v.w;
                }
            }
        }
    }
#pragma unroll
    for (int r = 0; r < BN / 128; r++) {
        if (TYPE != T_OPROJ) {
            if (lane == 0) bulk_wait_read0();
            bar_sync(1 + cw, 128);
        }
#pragma unroll
        for (int j = 0; j < 16; j += 2) {
            float v[8];
#pragma unroll
            for (int i = 0; i < 8; i++) v[i] = acc[(r * 16 + j) * 4 + i];
            const int tl = j + (lane >> 4);
            const uint32_t addr = stg + (tl >> 3) * 8192 + srow * 128 + (((tl & 7) ^ (srow & 7)) << 4);
            if (TYPE != T_OPROJ) {
                const bf16* bias = p.bias[TYPE == T_FFN1 ? 0 : 1];
                const uint32_t b0 = *(const uint32_t*)(bias + n0 + r * 128 + j * 8 + 2 * t);
                const uint32_t b1 = *(const uint32_t*)(bias + n0 + r * 128 + j * 8 + 8 + 2 * t);
                v[0] += bf_lo(b0); v[1] += bf_hi(b0); v[2] += bf_lo(b0); v[3] += bf_hi(b0);
                v[4] += bf_lo(b1); v[5] += bf_hi(b1); v[6] += bf_lo(b1); v[7] += bf_hi(b1);
                if (TYPE == T_FFN1) {
#pragma unroll
                    for (int i = 0; i < 8; i++) { const float q = v[i] > 0.f ? v[i] : 0.f; v[i] = q * q; }
                }
            } else {
                uint32_t d[4];
                ldsm4(d, addr);
                v[0] = g0 * v[0] + (1.f - g0) * bf_lo(d[0]); v[1] = g0 * v[1] + (1.f - g0) * bf_hi(d[0]);
                v[2] = g1 * v[2] + (1.f - g1) * bf_lo(d[1]); v[3] = g1 * v[3] + (1.f - g1) * bf_hi(d[1]);
                v[4] = g0 * v[4] + (1.f - g0) * bf_lo(d[2]); v[5] = g0 * v[5] + (1.f - g0) * bf_hi(d[2]);
                v[6] = g1 * v[6] + (1.f - g1) * bf_lo(d[3]); v[7] = g1 * v[7] + (1.f - g1) * bf_hi(d[3]);
            }
            stsm4(addr, pack_bf16(v[0], v[1]), pack_bf16(v[2], v[3]), pack_bf16(v[4], v[5]), pack_bf16(v[6], v[7]));
        }
        fence_async_smem();
        bar_sync(1 + cw, 128);
        if (leader) {
            tma_store_2d(&p.tmC[TYPE], n0 + r * 128, m0 + cw * 64, stg);
            tma_store_2d(&p.tmC[TYPE], n0 + r * 128 + 64, m0 + cw * 64, stg + 8192);
            bulk_commit();
        }
    }
}

__global__ void __launch_bounds__(384, 1) worker_kernel(const __grid_constant__ WorkParams p) {
    extern __shared__ uint8_t smem_raw[];
    const uint32_t sb = (smem_u32(smem_raw) + 1023) & ~1023u;
    const uint32_t s_stg = sb + WK_NST * WK_STAGE;
    const uint32_t bars = s_stg + 32768;
    const int tid = threadIdx.x, wg = tid >> 7, lane = tid & 31;
    if (tid == 0) {
        for (int i = 0; i < WK_NST; i++) { mbar_init(bars + 8 * i, 1); mbar_init(bars + 32 + 8 * i, 2); }
        for (int i = 0; i < 2; i++) { mbar_init(bars + 64 + 8 * i, 1); mbar_init(bars + 80 + 8 * i, 1); mbar_init(bars + 96 + 8 * i, 8); }
        asm volatile("fence.mbarrier_init.release.cluster;" ::: "memory");
    }
    __syncthreads();
    if (wg == 0) {
        reg_dec<40>();
        if (tid == 0) {
            int st = 0, ph = 1;
            bool ffn_left = true;
            if (WK_DELAY > 0 && blockIdx.x < 36) __nanosleep(WK_DELAY);
            for (uint32_t n = 0;; n++) {
                mbar_wait(bars + 96 + 8 * (n & 1), ((n >> 1) & 1) ^ 1);
                const uint32_t task = pick_task(ffn_left, n == 0 && blockIdx.x < 36);
                sts32(bars + 112 + 4 * (n & 1), task);
                mbar_arrive(bars + 80 + 8 * (n & 1));
                const int type = task & 255;
                if (type == T_DONE) break;
                if (type == T_GATE) {
                    mbar_wait(bars + 96 + 8 * (n & 1), (n >> 1) & 1);
                    continue;
                }
                asm volatile("fence.proxy.async.global;" ::: "memory");
                if (type == T_XATT) {
                    const int h0 = ((task >> 8) & 255) * NH + ((task >> 16) & 255) * 8;
                    for (int h = h0; h < h0 + 8; h++) {
                        mbar_wait(bars + 32 + 8 * st, ph);
                        const uint32_t a = sb + st * WK_STAGE, fb = bars + 8 * st;
                        mbar_expect_tx(fb, 28672);
                        bulk_load(a, (const char*)g_qkv + (size_t)h * 24576, 24576, fb);
                        bulk_load(a + 24576, (const char*)g_kvmem + (size_t)h * 4096, 4096, fb);
                        if (++st == WK_NST) { st = 0; ph ^= 1; }
                    }
                    continue;
                }
                const int m0 = ((task >> 8) & 255) * 128, nbx = type == T_OPROJ ? 2 : 4, n0 = ((task >> 16) & 255) * nbx * 64;
                const int kb0 = ((task >> 24) & 3) * 16;
                const int kbs = kb0 + (type == T_FFN1 ? 16 : (type == T_FFN2 ? 56 : 16 * (task >> 26)));
                const CUtensorMap* ta = &p.tmA[type];
                const CUtensorMap* tb = &p.tmB[type];
                for (int kb = kb0; kb < kbs; kb++) {
                    mbar_wait(bars + 32 + 8 * st, ph);
                    const uint32_t a = sb + st * WK_STAGE, fb = bars + 8 * st;
                    mbar_expect_tx(fb, 16384 + nbx * 8192);
                    tma_load_2d(a, ta, kb * 64, m0, fb);
                    for (int j = 0; j < nbx; j++) tma_load_2d(a + 16384 + j * 8192, tb, n0 + j * 64, kb * 64, fb);
                    if (++st == WK_NST) { st = 0; ph ^= 1; }
                }
            }
        }
    } else {
        reg_inc<232>();
        const int cw = wg - 1, warp = (tid >> 5) & 3;
        const bool leader = (tid & 127) == 0;
        const uint32_t stg = s_stg + cw * 16384;
        int st = 0, ph = 0, dph = 0;
        int pend = -1;
        for (uint32_t n = 0;; n++) {
            if (pend >= 0 && !mbar_try(bars + 80 + 8 * (n & 1), (n >> 1) & 1)) {
                bulk_wait0(); signal_cnt(pend); pend = -1;
            }
            mbar_wait(bars + 80 + 8 * (n & 1), (n >> 1) & 1);
            const uint32_t task = lds32(bars + 112 + 4 * (n & 1));
            const int type = task & 255, mb = (task >> 8) & 255, nb = (task >> 16) & 255;
            __syncwarp();
            if (lane == 0 && type != T_GATE) mbar_arrive(bars + 96 + 8 * (n & 1));
            if (pend >= 0 && type >= T_XATT) { bulk_wait0(); signal_cnt(pend); pend = -1; }
            __syncwarp();
            if (type == T_DONE) break;
            if (type == T_FFN1) { gemm_tile<T_FFN1>(p, sb, bars, stg, mb * 128, nb, cw, warp, lane, leader, st, ph, dph, 4, pend); if (leader) pend = C_F1 + mb; }
            else if (type == T_FFN2) { gemm_tile<T_FFN2>(p, sb, bars, stg, mb * 128, nb, cw, warp, lane, leader, st, ph, dph, 4, pend); if (leader) pend = C_F2 + mb; }
            else if (type == T_OPROJ) gemm_tile<T_OPROJ>(p, sb, bars, stg, mb * 128, nb, cw, warp, lane, leader, st, ph, dph, task >> 26, pend);
            else if (type == T_XATT) {
                if (lane == 0) bulk_wait_read0();
                bar_sync(1 + cw, 128);
                const int ms = (st + warp) & 3;
#pragma unroll 1
                for (int r = 0; r < 2; r++) {
                    mbar_wait(bars + 8 * ms, ph ^ r ^ (st + warp >= WK_NST));
                    if ((cw ^ r) == 0) xattn_warp<0>(sb + ms * WK_STAGE, bars + 32 + 8 * ms, mb, nb * 8 + r * 4 + warp, lane, stg + warp * 4096, &p.tmO16);
                    else xattn_warp<1>(sb + ms * WK_STAGE, bars + 32 + 8 * ms, mb, nb * 8 + r * 4 + warp, lane, stg + warp * 4096, &p.tmO16);
                }
                if (lane == 0) pend = C_XA + (mb >> 2);
            } else {
                uint4 gv[4];
#pragma unroll
                for (int i = 0; i < 4; i++) gv[i] = ((const uint4*)p.gw)[i * 32 + lane];
                const int row0 = mb * 128 + (cw * 4 + warp) * 16;
#pragma unroll 4
                for (int r = 0; r < 16; r++) {
                    const uint4* xr = (const uint4*)(p.x + (size_t)(row0 + r) * DM);
                    float acc = 0.f;
#pragma unroll
                    for (int i = 0; i < 4; i++) {
                        const uint4 a = xr[i * 32 + lane], b = gv[i];
                        acc += bf_lo(a.x) * bf_lo(b.x) + bf_hi(a.x) * bf_hi(b.x) + bf_lo(a.y) * bf_lo(b.y) + bf_hi(a.y) * bf_hi(b.y);
                        acc += bf_lo(a.z) * bf_lo(b.z) + bf_hi(a.z) * bf_hi(b.z) + bf_lo(a.w) * bf_lo(b.w) + bf_hi(a.w) * bf_hi(b.w);
                    }
#pragma unroll
                    for (int o = 16; o > 0; o >>= 1) acc += __shfl_xor_sync(~0u, acc, o);
                    if (lane == 0) g_gate[row0 + r] = 1.f / (1.f + __expf(-acc));
                }
                if (lane == 0) { mbar_arrive(bars + 96 + 8 * (n & 1)); signal_cnt(C_F2 + mb); }
            }
        }
        if (lane == 0) bulk_wait0();
        asm volatile("griddepcontrol.wait;" ::: "memory");
        bar_sync(3, 256);
        if (tid == 128) {
            __threadfence();
            sts32(bars + 120, atomicAdd(&g_cnt[C_DONE * 32], 1));
        }
        bar_sync(3, 256);
        if (lds32(bars + 120) == gridDim.x - 1) {
            __threadfence();
            for (int i = tid - 128; i < C_N * 32; i += 256) g_cnt[i] = 0;
        }
    }
}

struct ChainParams {
    CUtensorMap tmW[3];
    CUtensorMap tmWo;
    CUtensorMap tmX;
    const bf16* mem0;
    char* xmem;
    char* xpart;
    uint32_t zero;
};
constexpr uint32_t SB = 1024;
constexpr uint32_t CH_WS = SB;
constexpr uint32_t CH_WO = CH_WS + 65536;
constexpr uint32_t CH_W2 = CH_WO + 90112;
constexpr uint32_t CH_RING = CH_W2 + 8192;
constexpr uint32_t CH_MEMR = CH_RING + 24576;
constexpr uint32_t CH_KX = CH_MEMR + 12288;
constexpr uint32_t CH_VX = CH_KX + 8192;
constexpr uint32_t CH_QKV = CH_VX + 8192;
constexpr uint32_t CH_O = CH_QKV + 6144;
constexpr uint32_t CH_S = CH_O + 2048;
constexpr uint32_t CH_L = CH_RING + 65536;
constexpr uint32_t CH_BAR = CH_L + 64;
constexpr uint32_t CH_TS = CH_BAR + 256;
constexpr int CH_SMEM = CH_TS + 128 - SB;
constexpr uint32_t B_DHOP = CH_BAR, B_KV = CH_BAR + 8, B_WS = CH_BAR + 16, B_WO = CH_BAR + 24, B_PF = CH_BAR + 32, B_PE = CH_BAR + 64;
constexpr uint32_t B_XFA = CH_BAR + 128, B_XFK = CH_BAR + 136, B_XFS = CH_BAR + 144;
constexpr uint32_t B_E1 = CH_BAR + 152, B_E3 = CH_BAR + 160, B_E4 = CH_BAR + 168, B_FREE = CH_BAR + 176, B_E2 = CH_BAR + 184, B_ST = CH_BAR + 192;
enum { NB_S0 = 1, NB_S1, NB_S2, NB_W0, NB_W1, NB_W2, NB_M0, NB_M1, NB_X, NB_Y, NB_F, NB_Z, NB_R, NB_L };
constexpr uint32_t L2_HASH = 0xB3000;

#define TSTAMP(i)
#define PSTAMP(i)
#define XSTAMP(i)
#define XCNT(i, e) (void)(e)
#define TSTAMPD(i, dep)

__device__ __forceinline__ uint32_t umax4(uint4 v) { return __vimax3_u32(__vimax3_u32(v.x, v.y, v.z), v.w, 0u); }
__device__ __forceinline__ void lds128(uint32_t* r, uint32_t a) {
    asm volatile("ld.shared.v4.u32 {%0,%1,%2,%3}, [%4];" : "=r"(r[0]), "=r"(r[1]), "=r"(r[2]), "=r"(r[3]) : "r"(a) : "memory");
}
__device__ __forceinline__ uint32_t opaque(uint32_t x) { uint32_t y; asm volatile("mov.u32 %0, %1;" : "=r"(y) : "r"(x)); return y; }
__device__ __forceinline__ void delay(uint32_t n) {
    const uint32_t t0 = clk32();
    while (clk32() - t0 < n) {}
}
__device__ __forceinline__ uint32_t gtick() { uint32_t t; asm volatile("mov.u32 %0, %%globaltimer_lo;" : "=r"(t)::"memory"); return t >> 5; }
__device__ __forceinline__ void until_tick(uint32_t t) {
    while (((t - gtick() - 1) & 0x7FFFFFF) < 128) {}
}
__device__ __forceinline__ uint32_t sched_fence() {
    uint32_t c;
    asm volatile("mov.u32 %0, %%clock;" : "=r"(c)::"memory");
    return c;
}
__device__ __forceinline__ void until(uint32_t t) { while (t - clk32() - 1 < 8192) {} }
#define C_R 2760
#define C_W 340
#define C_S 1170
#define C_V 0
#define D_ST 0
#define G_T 22
#define PLAY 1
#define OPF 4
#define OBLK 0
#define DLY_L 40
#define SWM 0
#define WO_AT 11
#define XK0 0
#define EPI 2
#define FPOS 0
#define LPOS 4
#define NOXO 0
#define NPOLL 4
#define PACE 0
#define NOSH 0
#define XSM 10
#define DLY_K 0
#define XKC 3
#define OORD 0
#define CORD 1
#define FLIPP 0
#define FLIPM 0
#define NCH 2
#define PFM 1
#define PFD 4
#define RCP 1
#define CTRL 0
#define NOMASK 0
#define APOS 7
#define OF2 0
#define DRAIN 0
#define NPROBE 2
#define DLY_R 350
#define DLY_S2 400
#define DLY_S 400
__device__ __forceinline__ uint32_t probe_lat(char* q, uint32_t fill) {
    asm volatile("st.global.v4.u32 [%0], {%1,%1,%1,%1}; st.global.v4.u32 [%0+16], {%1,%1,%1,%1};" ::"l"(q), "r"(fill) : "memory");
    uint32_t best = ~0u;
#pragma unroll 1
    for (int r = 0; r < NPROBE; r++) {
        const uint32_t c0 = clk32();
        uint32_t v;
        asm volatile("atom.relaxed.gpu.global.or.b32 %0, [%1], 0;" : "=r"(v) : "l"(q) : "memory");
        if (v == 0x9e3779b9u) __nanosleep(20);
        best = min(best, clk32() - c0);
    }
    return best;
}

__device__ __forceinline__ void e_bulk(uint32_t dst, const void* src, uint32_t bytes, uint32_t bar) {
    asm volatile("{.reg .pred q; elect.sync _|q, 0xffffffff;\n"
                 "@q cp.async.bulk.shared::cluster.global.mbarrier::complete_tx::bytes [%0], [%1], %2, [%3];}"
                 ::"r"(dst), "l"(src), "r"(bytes), "r"(bar) : "memory");
}
__device__ __forceinline__ void ld_piece(uint2& v, const void* p) {
    asm volatile("{.reg .b64 a; ld.relaxed.gpu.global.b64 a, [%2]; mov.b64 {%0,%1}, a;}" : "=r"(v.x), "=r"(v.y) : "l"(p) : "memory");
}
__device__ __forceinline__ uint32_t reduce_task(const char* src, char* dst, uint32_t x, bool hi, uint32_t buf, uint32_t l16) {
    uint2 v[8];
    uint32_t it = 0;
    while (true) {
#pragma unroll
        for (int j = 0; j < 4; j++) asm volatile("cp.async.cg.shared.global [%0], [%1], 16;" ::"r"(buf + l16 + j * 512), "l"(src + j * 512) : "memory");
        asm volatile("cp.async.wait_all;" ::: "memory");
        __syncwarp();
#pragma unroll
        for (int j = 0; j < 8; j++) asm volatile("ld.shared.v2.u32 {%0,%1}, [%2];" : "=r"(v[j].x), "=r"(v[j].y) : "r"(buf + (l16 >> 1) + j * 256) : "memory");
        const float a = ((bf_lo(v[0].x) + bf_lo(v[1].x)) + (bf_lo(v[2].x) + bf_lo(v[3].x))) + ((bf_lo(v[4].x) + bf_lo(v[5].x)) + (bf_lo(v[6].x) + bf_lo(v[7].x)));
        const float c = ((bf_hi(v[0].x) + bf_hi(v[1].x)) + (bf_hi(v[2].x) + bf_hi(v[3].x))) + ((bf_hi(v[4].x) + bf_hi(v[5].x)) + (bf_hi(v[6].x) + bf_hi(v[7].x)));
        const float b = ((bf_lo(v[0].y) + bf_lo(v[1].y)) + (bf_lo(v[2].y) + bf_lo(v[3].y))) + ((bf_lo(v[4].y) + bf_lo(v[5].y)) + (bf_lo(v[6].y) + bf_lo(v[7].y)));
        const float d = ((bf_hi(v[0].y) + bf_hi(v[1].y)) + (bf_hi(v[2].y) + bf_hi(v[3].y))) + ((bf_hi(v[4].y) + bf_hi(v[5].y)) + (bf_hi(v[6].y) + bf_hi(v[7].y)));
        float k0 = hi ? b : a, k1 = hi ? d : c;
        k0 += __shfl_xor_sync(~0u, hi ? a : b, 8); k1 += __shfl_xor_sync(~0u, hi ? c : d, 8);
        uint32_t t;
        asm("{.reg .b32 a, b, c, d; lop3.b32 a, %1, %2, %9, 0x7E; lop3.b32 b, %3, %4, %9, 0x7E; lop3.b32 c, %5, %6, %9, 0x7E; lop3.b32 d, %7, %8, %9, 0x7E;\n"
            "lop3.b32 a, a, b, c, 0xFE; lop3.b32 %0, a, d, 1, 0xA8;}" : "=r"(t)
            : "r"(v[0].x), "r"(v[1].x), "r"(v[2].x), "r"(v[3].x), "r"(v[4].x), "r"(v[5].x), "r"(v[6].x), "r"(v[7].x), "r"(x));
        const bool bad = __any_sync(~0u, t);
        k0 += __shfl_xor_sync(~0u, k0, 16); k1 += __shfl_xor_sync(~0u, k1, 16);
        if (!bad) { st_relaxed32(dst, pack_bf16(k0, k1)); break; }
        if (++it > (1u << 22)) __trap();
    }
    return it;
}
template <int W>
__device__ __forceinline__ uint32_t stage_task(const char* img, uint32_t cb, uint32_t l16, uint32_t& ph) {
    const uint32_t dst = cb + (W < 2 ? CH_MEMR + W * 6144 : CH_RING + 4096), bar = cb + B_ST + 8 * W;
    const uint32_t chk = dst + 2 * l16 + ((l16 >> 4) & 28);
    uint32_t it = 0;
    while (true) {
        asm volatile("{.reg .pred q; elect.sync _|q, 0xffffffff; @q mbarrier.arrive.expect_tx.shared::cta.b64 _, [%0], %1;}" ::"r"(bar), "r"(W < 2 ? 6144 : 4096) : "memory");
        if (W == 0) { e_bulk(dst, img, 4096, bar); e_bulk(dst + 4096, img + 16384, 2048, bar); }
        if (W == 1) { e_bulk(dst, img + 16384 + 2048, 2048, bar); e_bulk(dst + 2048, img + 32768, 4096, bar); }
        if (W == 2) {
#pragma unroll
            for (int j = 0; j < 4; j++) e_bulk(dst + j * 5120, img + 49152 + j * 1024, 1024, bar);
        }
        mbar_wait(bar, ph);
        ph ^= 1;
        uint32_t m = 0;
#pragma unroll
        for (int j = 0; j < (W < 2 ? 6 : 4); j += 2) m = __vimax3_u32(m, lds32(chk + j * (W < 2 ? 1024 : 5120)), lds32(chk + (j + 1) * (W < 2 ? 1024 : 5120)));
        if (!__any_sync(~0u, m == 0xFFFFFFFFu)) break;
        if (++it > (1u << 22)) __trap();
    }
    return it;
}
#define PIN(v) asm volatile("{.reg .pred p; setp.eq.u32 p, %0, 0x9e3779b9; @p st.shared.u32 [%1], %0;}" ::"r"((uint32_t)(v)), "r"(cb + CH_BAR + 248) : "memory")
#define AFTER_BAR(s) do { if (opaque(s) == 0x9e3779b9u) __nanosleep(1); } while (0)
#define CNT(i, e) (e)
__device__ __forceinline__ uint32_t step_off(int s) { return (s & 1) * 8192 + (s >> 1) * 65536; }

__host__ __device__ constexpr int res_idx(int k) { return k < 4 ? k : (k < 6 ? 0 : k - 2); }
__host__ __device__ constexpr uint32_t xaddr(int c) {
    return c < 3 ? CH_MEMR + c * 4096 : c < 7 ? CH_RING + (c - 3) * 5120 : c < 11 ? CH_KX + (c - 7) * 4096 : c == 11 ? CH_RING + 20480 : CH_RING + (c - 12) * 5120;
}
__device__ __forceinline__ void tma_load_2d_mc(uint32_t dst, const CUtensorMap* tm, int c0, int c1, uint32_t bar) {
    asm volatile("cp.async.bulk.tensor.2d.shared::cluster.global.mbarrier::complete_tx::bytes.multicast::cluster [%0], [%1, {%3, %4}], [%2], %5;"
                 ::"r"(dst), "l"(tm), "r"(bar), "r"(c0), "r"(c1), "h"((uint16_t)7) : "memory");
}
__device__ __forceinline__ void bulk_load_mc(uint32_t dst, const void* src, uint32_t bytes, uint32_t bar) {
    asm volatile("cp.async.bulk.shared::cluster.global.mbarrier::complete_tx::bytes.multicast::cluster [%0], [%1], %2, [%3], %4;"
                 ::"r"(dst), "l"(src), "r"(bytes), "r"(bar), "h"((uint16_t)7) : "memory");
}
__device__ __forceinline__ void e_tma_mc(uint32_t dst, const CUtensorMap* tm, int c0, int c1, uint32_t bar) {
    asm volatile("{.reg .pred q; elect.sync _|q, 0xffffffff;\n"
                 "@q cp.async.bulk.tensor.2d.shared::cluster.global.mbarrier::complete_tx::bytes.multicast::cluster [%0], [%1, {%3, %4}], [%2], %5;}"
                 ::"r"(dst), "l"(tm), "r"(bar), "r"(c0), "r"(c1), "h"((uint16_t)7) : "memory");
}
__device__ __forceinline__ void e_bulk_mc(uint32_t dst, const void* src, uint32_t bytes, uint32_t bar) {
    asm volatile("{.reg .pred q; elect.sync _|q, 0xffffffff;\n"
                 "@q cp.async.bulk.shared::cluster.global.mbarrier::complete_tx::bytes.multicast::cluster [%0], [%1], %2, [%3], %4;}"
                 ::"r"(dst), "l"(src), "r"(bytes), "r"(bar), "h"((uint16_t)7) : "memory");
}
__device__ __forceinline__ void e_expect_tx(uint32_t bar, uint32_t bytes) {
    asm volatile("{.reg .pred q; elect.sync _|q, 0xffffffff; @q mbarrier.arrive.expect_tx.shared::cta.b64 _, [%0], %1;}" ::"r"(bar), "r"(bytes) : "memory");
}
__device__ __forceinline__ void tma_prefetch_2d(const CUtensorMap* tm, int c0, int c1) {
    asm volatile("cp.async.bulk.prefetch.tensor.2d.L2.global.tile [%0, {%1, %2}];" ::"l"(tm), "r"(c0), "r"(c1) : "memory");
}
__device__ __forceinline__ void arrive_remote(uint32_t a) { asm volatile("mbarrier.arrive.shared::cluster.b64 _, [%0];" ::"r"(a) : "memory"); }
__device__ __forceinline__ bool mbar_test(uint32_t bar, uint32_t parity) {
    uint32_t ok;
    asm volatile("{.reg .pred p; mbarrier.test_wait.parity.shared::cta.b64 p, [%1], %2; selp.u32 %0, 1, 0, p;}"
                 : "=r"(ok) : "r"(bar), "r"(parity) : "memory");
    return ok;
}
__device__ __forceinline__ void st_async2(uint32_t a, uint32_t v0, uint32_t v1, uint32_t bar) {
    asm volatile("st.async.shared::cluster.mbarrier::complete_tx::bytes.u32 [%0], %1, [%3];\n"
                 "st.async.shared::cluster.mbarrier::complete_tx::bytes.u32 [%0+128], %2, [%3];" ::"r"(a), "r"(v0), "r"(v1), "r"(bar) : "memory");
}
__device__ __forceinline__ void load_scores(float* e, float& ms, uint32_t l16) {
#pragma unroll
    for (int j = 0; j < 5; j++) {
        float4 v;
        asm volatile("ld.shared.v4.f32 {%0,%1,%2,%3}, [%4];" : "=f"(v.x), "=f"(v.y), "=f"(v.z), "=f"(v.w) : "r"(CH_S + j * 512 + l16) : "memory");
        e[2 * j] = v.x + v.z; e[2 * j + 1] = v.y + v.w;
    }
    float m = fmaxf(fmaxf(fmaxf(e[0], e[1]), fmaxf(e[2], e[3])), fmaxf(fmaxf(e[4], e[5]), fmaxf(e[6], e[7])));
    m = fmaxf(m, fmaxf(e[8], e[9]));
    m = fmaxf(m, __shfl_xor_sync(~0u, m, 1));
    m = fmaxf(m, __shfl_xor_sync(~0u, m, 2));
    ms = m * SM_SCALE_LOG2;
}
__device__ __forceinline__ uint32_t keep(uint32_t v, uint32_t z) { asm volatile("add.u32 %0, %0, %1;" : "+r"(v) : "r"(z)); return v; }
__device__ __forceinline__ uint64_t keep2(uint32_t a, uint32_t b, uint32_t z) { return (uint64_t)keep(a, z) | ((uint64_t)keep(b, z) << 32); }
__device__ __forceinline__ void stg64(void* p, uint32_t a, uint32_t b) { asm volatile("st.global.v2.u32 [%0], {%1,%2};" ::"l"(p), "r"(a), "r"(b) : "memory"); }
__device__ __forceinline__ void stg128(void* p, uint32_t a, uint32_t b, uint32_t c, uint32_t d) {
    asm volatile("st.global.v4.u32 [%0], {%1,%2,%3,%4};" ::"l"(p), "r"(a), "r"(b), "r"(c), "r"(d) : "memory");
}
__device__ __forceinline__ uint32_t movm(uint32_t x) {
    uint32_t y;
    asm volatile("movmatrix.sync.aligned.m8n8.trans.b16 %0, %1;" : "=r"(y) : "r"(x));
    return y;
}
__device__ __forceinline__ void st_async128(uint32_t a, uint4 v, uint32_t bar) {
    asm volatile("st.async.shared::cluster.mbarrier::complete_tx::bytes.v4.u32 [%0], {%1,%2,%3,%4}, [%5];"
                 ::"r"(a), "r"(v.x), "r"(v.y), "r"(v.z), "r"(v.w), "r"(bar) : "memory");
}

__global__ void __launch_bounds__(384, 1) chain_kernel(const __grid_constant__ ChainParams p) {
    extern __shared__ uint8_t smem_raw[];
    const int tid = threadIdx.x;
    const int warp = __shfl_sync(~0u, tid >> 5, 0);
    const int lane = __shfl_sync(~0u, tid & 31, tid & 31);
    uint32_t rank;
    asm volatile("mov.u32 %0, %%cluster_ctarank;" : "=r"(rank));
    rank = __shfl_sync(~0u, rank, 0);
    const int head = blockIdx.x / 3;
    const uint32_t cb = smem_u32(smem_raw) - SB;
    const int n2 = rank == 0 ? 6 : 5;
    const int b2 = rank == 0 ? 48 : (rank == 1 ? 54 : 59);
    if (tid == 0) {
        if (cb & 0xFFFFFF) __trap();
        for (int i = 0; i < 8; i++) mbar_init(cb + CH_BAR + 8 * i, i == 0 ? 9 : 1);
        for (int i = 8; i < 12; i++) mbar_init(cb + CH_BAR + 8 * i, 8);
        for (int i = 0; i < 3; i++) { mbar_init(cb + B_XFA + 8 * i, 1); mbar_init(cb + B_E1 + 8 * i, i == 0 ? 3 : 6); }
        mbar_init(cb + B_FREE, 3);
        mbar_init(cb + B_E2, 6);
        for (int i = 0; i < 3; i++) mbar_init(cb + B_ST + 8 * i, 1);
        asm volatile("fence.mbarrier_init.release.cluster;" ::: "memory");
    }
    asm volatile("griddepcontrol.launch_dependents;" ::: "memory");
    asm volatile("barrier.cluster.arrive.aligned; barrier.cluster.wait.aligned;" ::: "memory");
    if (warp < 8) {
        if (warp < 4 && lane == 0)
            sts32(cb + CH_BAR + 224 + warp * 4, probe_lat((warp < 2 ? p.xmem : p.xpart) + (warp & 1) * 4096 + blockIdx.x * 32, warp < 2 ? ~0u : 0u));
        bar_sync(NB_M1, 256);
    }
    if (warp >= 8) {
        reg_dec<40>();
        const int cta = blockIdx.x;
        if (warp == 11 && lane == 0) {
            const CUtensorMap* tw = &p.tmW[rank];
            for (int c = 0; c < 12; c++) {
                const int st = c & 3;
                if (c >= 4) mbar_wait(cb + B_PE + 8 * st, ((c >> 2) - 1) & 1);
                mbar_expect_tx(cb + B_PF + 8 * st, 16384);
                tma_load_2d(cb + CH_RING + st * 16384, tw, head * 128, c * 64, cb + B_PF + 8 * st);
                tma_load_2d(cb + CH_RING + st * 16384 + 8192, tw, head * 128 + 64, c * 64, cb + B_PF + 8 * st);
                if (c == 3) {
                    if (cta < 64) tma_prefetch_2d(&p.tmX, (cta & 15) * 64, (cta >> 4) * SEG);
                    mbar_expect_tx(cb + B_WS, 65536);
                    for (int j = 0; j < 8; j++) tma_load_2d(cb + CH_WS + j * 8192, tw, head * 128 + (j & 1) * 64, 768 + (j >> 1) * 64, cb + B_WS);
                }
                if (c == WO_AT) {
                    mbar_expect_tx(cb + B_WO, (16 + n2) * 4096);
                    for (int j = 0; j < 16 + n2; j++) {
                        const int tile = j < 8 ? rank * 8 + j : (j < 16 ? 24 + rank * 8 + (j - 8) : b2 + (j - 16));
                        tma_load_2d(cb + CH_WO + j * 4096, &p.tmWo, tile * 16, head * 128, cb + B_WO);
                    }
                }
            }
        }
        __syncwarp();
        uint32_t a16 = lane * 16;
        if (warp < 11) {
            const int w = warp - 8;
            if (w == 0) {
                bar_sync(NB_Z, 288);
                if (lane == 0) {
                    mbar_expect_tx(cb + B_DHOP, 4096);
                    asm volatile("fence.release.gpu;" ::: "memory");
                    st_relaxed32(&g_cnt[C_PTAB * 32 + cta], 4 | (lds32(cb + CH_BAR + 228) < lds32(cb + CH_BAR + 224)) | ((lds32(cb + CH_BAR + 236) < lds32(cb + CH_BAR + 232)) << 1));
                }
                __syncwarp();
                uint32_t v0, v1, v2, it = 0;
                do {
                    v0 = ld_relaxed32(&g_cnt[C_PTAB * 32 + lane * 3]);
                    v1 = ld_relaxed32(&g_cnt[C_PTAB * 32 + lane * 3 + 1]);
                    v2 = ld_relaxed32(&g_cnt[C_PTAB * 32 + lane * 3 + 2]);
                    if (++it > (1u << 22)) __trap();
                } while (__any_sync(~0u, (v0 & v1 & v2) == 0));
                asm volatile("fence.acquire.gpu;" ::: "memory");
                const uint32_t rel = __popc(__ballot_sync(~0u, (v0 ^ (v0 >> 1)) & 1)) + __popc(__ballot_sync(~0u, (v1 ^ (v1 >> 1)) & 1)) +
                                     __popc(__ballot_sync(~0u, (v2 ^ (v2 >> 1)) & 1)) > 48;
                const uint32_t np = __ballot_sync(~0u, __popc((v0 ^ rel) & 3) + __popc((v1 ^ rel) & 3) + __popc((v2 ^ rel) & 3) > 3);
                sts32(cb + CH_BAR + 96, np);
                sts32(cb + CH_BAR + 112, ((np >> head) ^ rel) & 1);
                sts32(cb + CH_BAR + 116, (np >> head) & 1);
                PSTAMP(9);
            }
            if (w == 2) bar_arrive(NB_S2, 320);
            bar_sync(NB_R, 352);
            const uint32_t near = __shfl_sync(~0u, lds32(cb + CH_BAR + 112) | (lds32(cb + CH_BAR + 116) << 1), 0);
            {
                if (w < 2) bar_sync(NB_X + w, 288);
                const uint4* m0 = (const uint4*)p.mem0 + (lane & 7) * 128 + (lane >> 3) + w * 48;
                const uint32_t dst = w < 2 ? cb + CH_MEMR + w * 6144 + a16 : cb + CH_RING + 4096 + ((a16 & 112) << 3) + (((a16 >> 3) ^ a16) & 112);
#pragma unroll 4
                for (int j = 0; j < (w < 2 ? 12 : 8); j++) sts128(w < 2 ? dst + j * 512 : (dst ^ ((j & 1) * 64)) + (j >> 1) * 5120, m0[j * 4]);
                fence_async_smem();
                if (w < 2) bar_arrive(NB_S0 + w, 288); else bar_sync(NB_S2, 320);
            }
            uint32_t sph = 0;
            for (int s = 0; s < NSEG - 1; s++) {
                a16 += p.zero;
                if (w < 2) {
                    const uint32_t l16 = a16 + cb + w * 1024;
                    uint32_t q[2][4], kf[2][4];
                    float sc[2][4];
                    sc[0][0] = sc[0][1] = sc[0][2] = sc[0][3] = sc[1][0] = sc[1][1] = sc[1][2] = sc[1][3] = 0.f;
                    const uint32_t sa = cb + CH_S + 2048 + w * 8 + ((a16 & 48) << 3) + ((a16 >> 3) & 48) + ((a16 >> 4) & 4);
                    PIN(l16 ^ sa);
                    mbar_wait(cb + B_DHOP, s & 1);
#pragma unroll
                    for (int i = 0; i < 2; i++) { ldsm4t(q[i], CH_QKV + i * 512 + l16); ldsm4t(kf[i], CH_QKV + 2048 + i * 512 + l16); }
#pragma unroll
                    for (int i = 0; i < 2; i++) {
                        mma16816(sc[0], kf[i][0], kf[i][1], kf[i][2], kf[i][3], q[i][0], q[i][1]);
                        mma16816(sc[1], kf[i][0], kf[i][1], kf[i][2], kf[i][3], q[i][2], q[i][3]);
                    }
                    sts32(sa, __float_as_uint(sc[0][0] + sc[1][2])); sts32(sa + 64, __float_as_uint(sc[0][1] + sc[1][3]));
                    if (w == 0) {
                        bar_sync(NB_M0, 320);
                        AFTER_BAR(s);
                        delay(DLY_L);
                        float e[10], ms, l = 0.f;
                        load_scores(e, ms, l16);
#pragma unroll
                        for (int j = 0; j < 5; j++) {
                            const uint32_t pk = pack_bf16(ex2(fmaf(e[2 * j], SM_SCALE_LOG2, -ms)), ex2(fmaf(e[2 * j + 1], SM_SCALE_LOG2, -ms)));
                            l += bf_lo(pk) + bf_hi(pk);
                        }
                        l += __shfl_xor_sync(~0u, l, 1);
                        l += __shfl_xor_sync(~0u, l, 2);
                        sts32(cb + CH_L + ((l16 >> 3) & 48) + ((l16 >> 4) & 4), __float_as_uint(1.f / l));
                        bar_arrive(NB_L, 288);
                    } else {
                        bar_arrive(NB_M0, 320);
                    }
                } else {
                    sts32(cb + CH_BAR + 244, s);
                    const uint32_t t0 = gtick();
                    if (a16 < 256) st_relaxed32(p.xmem + (16384 + cta * 32) + (((a16 >> 2) & 28) + ((a16 & 128) << 5)), t0);
                    if (s + 4 < NSEG) {
                        if (cta < 16)
                            asm volatile("{.reg .pred q; elect.sync _|q, 0xffffffff; @q cp.async.bulk.prefetch.tensor.2d.L2.global.tile [%0, {%1, %2}];}"
                                         ::"l"(&p.tmX), "r"(cta * 64), "r"((s + 4) * SEG) : "memory");
                        if (cta < 64) asm volatile("prefetch.global.L2 [%0];" ::"l"(p.xmem + step_off(s + 4) + (cta >> 4) * 16384 + (cta & 15) * 512 + a16) : "memory");
                    }
                    until_tick(t0 + G_T);
                    const uint32_t c0 = clk32();
                    const uint32_t* tb = (const uint32_t*)(p.xmem + (16384 + (near & 1) * 4096) + a16 * 2);
                    const uint32_t g0_ = (t0 + G_T - ld_relaxed32(tb)) & 0x7FFFFFF, g1_ = (t0 + G_T - ld_relaxed32(tb + 256)) & 0x7FFFFFF,
                                   g2_ = (t0 + G_T - ld_relaxed32(tb + 512)) & 0x7FFFFFF;
                    sts32(cb + CH_BAR + 240, c0 - __reduce_min_sync(~0u, max(max(g0_, g1_), g2_) > 64 ? 4 : min(min(g0_, g1_), g2_)) * 57);
                }
                const uint32_t so = step_off(s + 1);
                const uint32_t o = (w * 96 + cta) * 8192;
                const uint32_t u = w < 2 ? (w * 24 + (cta >> 2)) * 256 + (cta & 3) * 32 : 12288 + (cta >> 4) * 1024 + (cta & 3) * 256 + (((cta >> 2) ^ cta) & 3) * 32;
                const char* rs = p.xpart + (o + ((__popc(o & L2_HASH) ^ (near >> 1)) & 1) * 4096) + (RCP ? a16 : a16 >> 1);
                char* rd = p.xmem + (so + (u >> 12) * 16384 + (u & 4095)) + (((a16 >> 2) & 12) + ((a16 & 256) << 4) +
                           (w < 2 ? ((a16 >> 3) & 16) + ((a16 << 1) & 128) : (a16 & 128) + (((a16 >> 2) ^ (a16 >> 3)) & 16)));
                const char* ss = p.xmem + (so + ((__popc(so & L2_HASH) ^ near) & 1) * 4096);
                PIN((uintptr_t)rs ^ (uintptr_t)rd ^ (uintptr_t)ss ^ (((uintptr_t)rs + (uintptr_t)rd + (uintptr_t)ss) >> 32));
                bar_sync(NB_W0, 384);
                const uint32_t t = lds32(cb + CH_BAR + 240) + C_R + w * C_W;
                if (w == 2) { XSTAMP(9); XCNT(10, t - C_R - 2 * C_W); }
                if (w > 0) bar_sync(NB_W0 + w, 288);
                if (w == 2) { XCNT(11, 0); XSTAMP(11); }
                if (w < 2 || cta < 64) {
                    until(t);
                    XSTAMP(16 + w * 4);
                    XCNT(w == 0 ? 12 : (w == 1 ? 15 : 31), reduce_task(rs, rd, (s & 1) ^ 1, a16 & 128, cb + CH_QKV + w * 2048, a16));
                }
                XSTAMP(17 + w * 4);
                if (w == 0 && a16 == 0) mbar_expect_tx(cb + B_DHOP, 4096);
                if (w < 2 && s + 2 < NSEG) bar_sync(NB_X + w, 288);
                until(t + C_S + w * C_V);
                XSTAMP(18 + w * 4);
                if (w == 0) XCNT(13, stage_task<0>(ss, cb, a16, sph));
                else if (w == 1) XCNT(14, stage_task<1>(ss, cb, a16, sph));
                else XCNT(30, stage_task<2>(ss, cb, a16, sph));
                XSTAMP(19 + w * 4);
                if (w < 2) bar_arrive(NB_S0 + w, 288); else bar_sync(NB_S2, 320);
            }
        } else {
            bar_sync(NB_W0, 288);
            for (int s = -2; s < NSEG; s++) {
                if (s >= -1) {
                    if (s + 1 < NSEG) {
                        mbar_wait(cb + B_E4, (s + 1) & 1);
                        e_expect_tx(cb + B_XFS, 16384);
                        e_tma_mc(cb + xaddr(12) + rank * 5120, &p.tmX, (12 + rank) * 64, (s + 1) * SEG, cb + B_XFS);
                        if (rank == 0) e_tma_mc(cb + xaddr(15), &p.tmX, 15 * 64, (s + 1) * SEG, cb + B_XFS);
                        mbar_wait(cb + B_E3, (s + 1) & 1);
                        if (s >= 0) {
                            e_expect_tx(cb + B_KV, 16384);
                            if (rank > 0) e_bulk_mc(cb + CH_KX - 8192 + rank * 8192, (const char*)g_qkv + (size_t)((s * NH + head) * 3 + rank) * 8192, 8192, cb + B_KV);
                        }
                        mbar_wait(cb + B_XFS, (s + 1) & 1);
                    }
                    bar_arrive(NB_S2, 320);
                }
                if (s + 2 < NSEG) {
                    mbar_wait(cb + B_E2, s & 1);
                    e_expect_tx(cb + B_XFA, 16384);
                    e_tma_mc(cb + xaddr(0) + rank * 4096, &p.tmX, rank * 64, (s + 2) * SEG, cb + B_XFA);
                    if (rank == 2) e_tma_mc(cb + xaddr(11), &p.tmX, 11 * 64, (s + 2) * SEG, cb + B_XFA);
                }
                if (s >= -1) {
                    bar_sync(NB_F, 288);
                }
                if (s >= -1) {
                    if (a16 == 0) {
                        if (s + 1 < NSEG) {
                            char* xd = (char*)g_qkv + (size_t)(((s + 1) * NH + head) * 3 + rank) * 8192;
                            bulk_store(xd, cb + xaddr(3), 4096);
                            bulk_store(xd + 4096, cb + xaddr(4), 4096);
                        }
                        if (s >= 0 && rank > 0) bulk_store((char*)g_kvmem + ((s * NH + head) * 2 + rank - 1) * 2048, cb + CH_QKV + rank * 2048, 2048);
                        bulk_commit();
                    }
                }
                __syncwarp();
                if (s + 2 < NSEG) {
                    e_expect_tx(cb + B_XFK, 32768);
                    if (a16 < 48) arrive_remote((a16 << 20) + B_FREE);
                    mbar_wait(cb + B_FREE, s & 1);
                    e_tma_mc(cb + (rank == 2 ? xaddr(10) : xaddr(5) + rank * 5120), &p.tmX, (rank == 2 ? 10 : 5 + rank) * 64, (s + 2) * SEG, cb + B_XFK);
                    e_tma_mc(cb + xaddr(7) + rank * 4096, &p.tmX, (7 + rank) * 64, (s + 2) * SEG, cb + B_XFK);
                }
                if (a16 == 0) bulk_wait_read0();
                __syncwarp();
                if (s >= 0 && s < NSEG - 1) bar_arrive(NB_W0, 384);
                if (s + 2 < NSEG) {
                    if (a16 < 32) arrive_remote((a16 << 20) + B_E1);
                    if (rank < 2) {
                        mbar_wait(cb + B_E1, s & 1);
                        e_tma_mc(cb + xaddr(3) + rank * 5120, &p.tmX, (3 + rank) * 64, (s + 2) * SEG, cb + B_XFK);
                    }
                }
                if (a16 == 0) {
                    bulk_wait0();
                    if (s >= 0) asm volatile("red.release.gpu.global.add.u32 [%0], 1;" ::"l"(&g_cnt[(C_SEG + s) * 32]) : "memory");
                }
                __syncwarp();
            }
        }
    } else {
        reg_inc<232>();
        uint32_t wr[46][4];
        uint32_t l16 = cb + lane * 16;
        {
            uint4* zm = (uint4*)p.xmem + blockIdx.x * 256 + tid;
#pragma unroll
            for (int i = 0; i < 6; i++)
                if (i < 5 || blockIdx.x < 32) zm[i * 24576] = make_uint4(~0u, ~0u, ~0u, ~0u);
            uint4* zp = (uint4*)p.xpart + blockIdx.x * 512 + tid;
#pragma unroll
            for (int i = 0; i < 6; i++)
                if (i < 4 || blockIdx.x < 64) zp[(i >> 1) * 49152 + (i & 1) * 256] = make_uint4(0, 0, 0, 0);
            bar_arrive(NB_Z, 288);
            PSTAMP(0);
            const int krow = (lane >> 4) * 8 + (lane & 7);
            const int ch = (warp & 3) * 2 + ((lane >> 3) & 1);
            const uint32_t off = (warp >> 2) * 8192 + krow * 128 + ((ch ^ (krow & 7)) << 4);
#pragma unroll
            for (int c = 0; c < 12; c++) {
                mbar_wait(cb + B_PF + 8 * (c & 3), (c >> 2) & 1);
                if (c == 0) PSTAMP(1);
                if (c == 4) PSTAMP(2);
                if (c == 11) PSTAMP(3);
#pragma unroll
                for (int k = 0; k < 4; k++) {
                    if (c != 1 || k >= 2) ldsm4t(wr[res_idx(c * 4 + k)], cb + CH_RING + (c & 3) * 16384 + off + k * 2048);
                    else {
                        uint32_t a[4];
                        lds128(a, l16 + CH_RING + 16384 + k * 8192 + warp * 512);
                        sts128(l16 + CH_W2 + k * 4096 + warp * 512, make_uint4(a[0], a[1], a[2], a[3]));
                    }
                }
                __syncwarp();
                if (lane == 0) mbar_arrive(cb + B_PE + 8 * (c & 3));
            }
            fence_async_smem();
            bar_sync(NB_W0, 288);
        }
#define XRELEASE(bar) do { const uint32_t _l = opaque(l16) & 0x1F0; if ((warp & 3) == 0 && _l < 48) arrive_remote((_l << 20) + (bar)); } while (0)
        if (mapa(B_E1, 2) != (2u << 24) + B_E1) __trap();
        XRELEASE(B_E2);
        uint32_t pinfo = (lane >> 2) * 8 + (lane & 3) * 8192 + 1;
        const uint64_t da = make_desc(CH_WS, 16, 1024, 1) + (warp >> 2) * 512;
        mbar_wait(cb + B_WS, 0);
        PSTAMP(4);
        uint32_t fend = 0;
        for (int s = -1; s < NSEG; s++) {
            l16 += p.zero;
            float xa[20];
            uint32_t wc[2][4];
            auto load_wc = [&]() {
                const uint32_t a = l16;
                const uint32_t w2 = cb + CH_W2 + (warp >> 2) * 4096 + ((a & 256) << 2) + ((a & 112) << 3) + ((((warp & 3) * 32 + ((a & 128) >> 3)) ^ a) & 112);
                ldsm4t(wc[0], w2); ldsm4t(wc[1], w2 + 2048);
            };
            if (s + 1 < NSEG) {

                mbar_wait(cb + B_XFA, (s + 1) & 1);
                wg_fence();
#pragma unroll
                for (int c = 0; c < 12; c++) {
                    if (c == XKC) { mbar_wait(cb + B_XFK, (s + 1) & 1); wg_fence(); }
#pragma unroll
                    for (int k = 0; k < 4; k++) {
                        const uint64_t dx = make_desc(xaddr(c), 16, 1024, 1) + k * 2;
                        if (c == 1 && k < 2) wgmma_ss_n32_t10(xa, make_desc(CH_W2, 16, 1024, 1) + (warp >> 2) * 256 + k * 128, dx, 1);
                        else if (!NOSH || k == 0) wgmma_rs_n32_t0(xa, wr[res_idx(c * 4 + k)], dx, (c | k) != 0);
                    }
                    if (c == 2 || c == 3 || c == 6 || c == 7 || c == 10 || c == 11) wg_commit();
                    if (c == 11) load_wc();
                    if (c == 3 || c == 7 || c == 11) {
                        wg_wait<1>();
                        if (c == 3) { if (s >= 0) { bar_arrive(NB_X, 288); bar_arrive(NB_Y, 288); } }
                        else XRELEASE(c == 7 ? B_E4 : B_E3);
                    }
                }
                wg_wait<0>();
            } else {
                wg_fence();
                wgmma_rs_n32_t0(xa, wr[0], make_desc(xaddr(11), 16, 1024, 1), 0);
                wg_commit();
                load_wc();
                wg_wait<0>();
            }
            TSTAMP(1);
            xa[16] = xa[17] = xa[18] = xa[19] = 0.f;
            if (s >= 0) {
                float acc[4] = {0.f, 0.f, 0.f, 0.f}, acc2[4] = {0.f, 0.f, 0.f, 0.f};
#define PAIR(i) ((i) == 0 ? 2 : (i) == 2 ? 0 : (i))
                constexpr int NB = 6 - NCH;
                uint32_t b[NB][4], fz[24];
                bar_sync(NB_S0, 288);
#pragma unroll
                for (int i = 0; i < NB; i++) ldsm4(b[i], l16 + CH_MEMR + PAIR(i) * 512);
                TSTAMP(0);
#pragma unroll
                for (int i = 0; i < 24; i++) {
                    const int k = PAIR(i) * 2;
                    const uint32_t* a0 = k == 4 ? wc[0] : wr[res_idx(k)];
                    const uint32_t* a1 = k == 4 ? wc[1] : wr[res_idx(k + 1)];
                    mma16816(NCH == 2 || i % 3 == 0 ? xa + 16 : (i % 3 == 1 ? acc2 : acc), a0[0], a0[1], a0[2], a0[3], b[i % NB][0], b[i % NB][1]);
                    mma16816(NCH == 2 || i % 3 == 0 ? acc : (i % 3 == 1 ? xa + 16 : acc2), a1[0], a1[1], a1[2], a1[3], b[i % NB][2], b[i % NB][3]);
                    fz[i] = 0;
                    if (i + NB < 24) {
                        if (CORD) fz[i] = sched_fence();
                        if (i + NB == 12) bar_sync(NB_S1, 288);
                        ldsm4(b[i % NB], l16 + CH_MEMR + PAIR(i + NB) * 512);
                    }
                }
                if (NCH == 3) { acc[0] += acc2[0]; acc[1] += acc2[1]; acc[2] += acc2[2]; acc[3] += acc2[3]; }
                xa[16] += acc[0]; xa[17] += acc[1]; xa[18] += acc[2]; xa[19] += acc[3];
                uint32_t fx = fend;
#pragma unroll
                for (int i = 0; i < 24; i++) fx ^= fz[i];
                pinfo += fx & p.zero;
            }

            bar_sync(NB_S2, 320);
            wg_fence();
#pragma unroll
            for (int k = 0; k < 16; k++) wgmma_ss_n40_t10(xa, da + (k >> 2) * 1024 + (k & 3) * 128, make_desc(xaddr(12 + (k >> 2)), 16, 1024, 1) + (k & 3) * 2, 1);
            wg_commit();
            if (s < NSEG - 1) XRELEASE(B_E2);
            const uint32_t lq = l16;
            auto put_out = [&]() {
                bar_sync(NB_M1, 256);
#pragma unroll
                for (int i = 0; i < 2; i++)
                    stsm4(lq + xaddr(3 + i) + warp * 512, pack_bf16(xa[8 * i], xa[8 * i + 1]), pack_bf16(xa[8 * i + 2], xa[8 * i + 3]),
                          pack_bf16(xa[8 * i + 4], xa[8 * i + 5]), pack_bf16(xa[8 * i + 6], xa[8 * i + 7]));
            };
            const uint32_t dq = ((lq >> 2) & 124) + CH_QKV + (rank == 1 ? 2048 + (warp >> 1) * 512 + (warp & 1) * 128 : rank * 2048 + warp * 256);
            const uint32_t dstep = rank == 1 ? 256 : 128;
            if (__builtin_expect(s < 0 || s == NSEG - 1, 0)) {
                wg_wait<0>();
                sts32(cb + dq, pack_bf16(xa[16], xa[17])); sts32(cb + dq + dstep, pack_bf16(xa[18], xa[19]));
                put_out();
                fence_async_smem();
                bar_arrive(NB_F, 288);
                if (s >= 0) break;
                mbar_wait(cb + B_WO, 0);
                const int ln = (l16 >> 4) & 31;
                const int krow = (ln >> 4) * 8 + (ln & 7);
                const uint32_t wt = cb + CH_WO + warp * 4096 + krow * 32 + ((((ln >> 3) & 1) ^ ((krow >> 2) & 1)) << 4);
#pragma unroll 1
                for (int i = 0; i < (warp < n2 ? 24 : 16); i++) {
                    uint32_t a[4];
                    const uint32_t o = (i >> 3) * 32768 + (i & 7) * 512;
                    ldsm4t(a, wt + o);
                    __syncwarp();
                    const uint32_t d = cb + CH_WO + warp * 4096 + o + (ln >> 3) * 64 + (ln & 3) * 16 + ((ln >> 2) & 1) * 4;
                    sts32(d, a[0]); sts32(d + 256, a[1]); sts32(d + 8, a[2]); sts32(d + 264, a[3]);
                }
                bar_sync(NB_R, 352);
#pragma unroll
                for (int w = 0; w < 3; w++) {
                    const int rc = ((w < 2 ? rank * 8 : (b2 - 48)) + warp) * 4 + (ln & 3);
                    const uint32_t v = lds32(cb + CH_BAR + 96) >> ((rc * 171) >> 9);
                    pinfo ^= ((__popc(((w * 96 + rc) * 8192) & L2_HASH) ^ v) & 1) * ((1u << (16 + w)) | (1u << (16 + (w + 2) % 3)) | (w == 0 ? 4096 : 0));
                }
                continue;
            }
            {
                mbar_wait(cb + B_KV, s & 1);
                const uint32_t z = (clk32() ^ lq) & p.zero;
                const uint32_t r1 = (rank == 2 ? 0 : rank + 1) << 24, r2 = (rank == 0 ? 2 : rank - 1) << 24;
                const uint64_t rd0 = keep2(dq + r1, B_DHOP + r1, z), rd1 = keep2(dq + dstep + r1, B_DHOP + r1, z);
                const uint64_t rd2 = keep2(dq + r2, B_DHOP + r2, z), rd3 = keep2(dq + dstep + r2, B_DHOP + r2, z);
                const uint32_t f0 = keep(warp < 4 ? lq + CH_VX + warp * 1024
                                                  : (lq & 0xFF000070u) + ((lq & 128) << 1) + ((lq & 256) >> 1) + CH_KX + ((warp & 1) * 8 + (warp & 2) * 2) * 512, z);
                const uint32_t sa = keep(cb + CH_S + (warp & 1) * 1024 + (warp & 2) * 4 + ((lq & 48) << 3) + ((lq >> 3) & 48) + ((lq >> 4) & 4), z);
                const uint32_t qa = keep(lq + CH_QKV + (warp & 2) * 512, z);
                uint32_t fw = sched_fence();
                wg_wait<0>();
                TSTAMP(3);
                const uint32_t w0 = pack_bf16(xa[16], xa[17]), w1 = pack_bf16(xa[18], xa[19]);
                st_async32((uint32_t)rd0, w0, rd0 >> 32); st_async32((uint32_t)rd1, w1, rd1 >> 32);
                st_async32((uint32_t)rd2, w0, rd2 >> 32); st_async32((uint32_t)rd3, w1, rd3 >> 32);
                sts32((uint32_t)rd2 + (cb - r2), w0); sts32((uint32_t)rd3 + (cb - r2), w1);
                __syncwarp();
                if ((lq & 0x1F0) == 0) mbar_arrive(cb + B_DHOP);
                put_out();
                uint32_t wa[4][4], fu = 0, fv = 0;
                if (warp < 4) {
                    uint32_t vm[4];
                    ldsm4(wa[0], f0); ldsm4(wa[1], f0 + 512); ldsm4(wa[2], f0 + 4096); ldsm4(wa[3], f0 + 4608);
                    fence_async_smem();
                    bar_arrive(NB_F, 288);
                    bar_sync(NB_M0, 320);
                    float e[10], ms;
                    load_scores(e, ms, lq);
                    ldsm4(vm, lq + CH_QKV + 4096 + warp * 512);
                    fu = sched_fence();
                    bar_arrive(NB_Z, 256);
                    fv = sched_fence();
                    uint32_t pp[5];
#pragma unroll
                    for (int j = 0; j < 5; j++) pp[j] = pack_bf16(ex2(fmaf(e[2 * j], SM_SCALE_LOG2, -ms)), ex2(fmaf(e[2 * j + 1], SM_SCALE_LOG2, -ms)));
                    float o0[4] = {0.f, 0.f, 0.f, 0.f}, o1[4] = {0.f, 0.f, 0.f, 0.f};
                    mma16816(o0, wa[0][0], wa[0][1], wa[0][2], wa[0][3], pp[0], pp[1]);
                    mma16816(o1, wa[1][0], wa[1][1], wa[1][2], wa[1][3], pp[0], pp[1]);
                    mma16816(o0, wa[2][0], wa[2][1], wa[2][2], wa[2][3], pp[2], pp[3]);
                    mma16816(o1, wa[3][0], wa[3][1], wa[3][2], wa[3][3], pp[2], pp[3]);
                    mma1688(o0, vm[0], vm[1], pp[4]);
                    mma1688(o1, vm[2], vm[3], pp[4]);
                    stsm4(lq + CH_O + warp * 512, pack_bf16(o0[0], o0[1]), pack_bf16(o0[2], o0[3]), pack_bf16(o1[0], o1[1]), pack_bf16(o1[2], o1[3]));
#pragma unroll
                    for (int i = 0; i < OPF; i++) lds128(wa[i], lq + CH_WO + warp * 4096 + i * 512);
                } else {
                    uint32_t q[2][4];
                    float sc[2][4];
                    sc[0][0] = sc[0][1] = sc[0][2] = sc[0][3] = sc[1][0] = sc[1][1] = sc[1][2] = sc[1][3] = 0.f;
#pragma unroll
                    for (int i = 0; i < 4; i++) ldsm4t(wa[i], f0 + i * 512);
                    fence_async_smem();
                    bar_arrive(NB_F, 288);
                    mbar_wait(cb + B_DHOP, s & 1);
                    ldsm4t(q[0], qa);
                    ldsm4t(q[1], qa + 512);
#pragma unroll
                    for (int i = 0; i < 4; i++) mma16816(sc[i & 1], wa[i][0], wa[i][1], wa[i][2], wa[i][3], q[i >> 1][(i & 1) * 2], q[i >> 1][(i & 1) * 2 + 1]);
                    sts32(sa, __float_as_uint(sc[0][0] + sc[1][0])); sts32(sa + 64, __float_as_uint(sc[0][1] + sc[1][1]));
                    sts32(sa + 512, __float_as_uint(sc[0][2] + sc[1][2])); sts32(sa + 576, __float_as_uint(sc[0][3] + sc[1][3]));
                    bar_arrive(NB_M0, 320);
                    bar_sync(NB_Z, 256);
#pragma unroll
                    for (int i = 0; i < OPF; i++) lds128(wa[i], lq + CH_WO + warp * 4096 + i * 512);
                }
                bar_sync(NB_M1, 256);
                uint32_t ob[4][4];
#pragma unroll
                for (int i = 0; i < 4; i++) ldsm4t(ob[i], lq + CH_O + i * 512);

                float ra, rb;
                uint32_t fz[3][9], fy[3][8];
                const uint32_t fl = sched_fence();
                const uint32_t wo = opaque(lq + warp * 4096);
#pragma unroll
                for (int w = 0; w < 3; w++) {
#pragma unroll
                    for (int j = 0; j < 9; j++) fz[w][j] = fy[w][j & 7] = 0;
                    if (w < 2 || warp < n2) {
                        float c[4] = {0.f, 0.f, 0.f, 0.f}, c2[4] = {0.f, 0.f, 0.f, 0.f};
                        char* dst;
#pragma unroll
                        for (int j = 0; j < 8; j++) {
                            const int cu = (w * 8 + j) % OPF;
                            mma16816(j & 1 ? c2 : c, wa[cu][0], wa[cu][1], wa[cu][2], wa[cu][3], ob[j >> 1][(j & 1) * 2], ob[j >> 1][(j & 1) * 2 + 1]);
                            const int nx = w * 8 + j + OPF;
                            if (nx < 24 || j == 7) fz[w][j] = sched_fence();
                            if (nx < 24) lds128(wa[nx % OPF], wo + CH_WO + (nx >> 3) * 32768 + (nx & 7) * 512);
                            if (OF2 && nx < 24) fy[w][j] = sched_fence();
                            if (w == 0 && j == LPOS) {
                                bar_sync(NB_L, 288);
                                lds64f(CH_L + (wo & 0xFF000030u), ra, rb);
                            }
                            if (j == APOS) dst = (p.xpart + (((w < 2 ? w * 24 + rank * 8 : b2) + warp) * 32768 + head * 64)) + (pinfo & 0xFFF8);
                        }
                        c[0] += c2[0]; c[1] += c2[1]; c[2] += c2[2]; c[3] += c2[3];
                        uint32_t p0;
                        asm("lop3.b32 %0, %1, %2, 1, 0xD8;" : "=r"(p0) : "r"(pack_bf16(c[0] * ra, c[2] * ra)), "r"(pinfo));
                        st_relaxed64(dst, p0, pack_bf16(c[1] * rb, c[3] * rb));
                        if (w < 2) { bar_arrive(NB_W0 + w, w == 0 ? 384 : 288); fz[w][8] = sched_fence(); }
                    }
                    pinfo ^= ((pinfo >> (4 + w)) & 4096) | (w == 2);
                }
                bar_arrive(NB_W2, 288);
                fend = fw ^ fu ^ fv ^ fl;
#pragma unroll
                for (int j = 0; j < 27; j++) fend ^= fz[j / 9][j % 9] ^ (j < 24 ? fy[j / 8][j & 7] : 0);
                l16 = wo - warp * 4096;
            }
        }
    }
    asm volatile("barrier.cluster.arrive.aligned; barrier.cluster.wait.aligned;" ::: "memory");
}

typedef CUresult (*EncodeFn)(CUtensorMap*, CUtensorMapDataType, cuuint32_t, void*, const cuuint64_t*, const cuuint64_t*,
                             const cuuint32_t*, const cuuint32_t*, CUtensorMapInterleave, CUtensorMapSwizzle,
                             CUtensorMapL2promotion, CUtensorMapFloatOOBfill);
static EncodeFn g_encode = nullptr;

static void make_map(CUtensorMap* tm, const void* ptr, uint64_t cols, uint64_t rows, uint32_t bc, uint32_t br, CUtensorMapSwizzle sw) {
    cuuint64_t dims[2] = {cols, rows};
    cuuint64_t strides[1] = {cols * 2};
    cuuint32_t box[2] = {bc, br};
    cuuint32_t es[2] = {1, 1};
    g_encode(tm, CU_TENSOR_MAP_DATA_TYPE_BFLOAT16, 2, (void*)ptr, dims, strides, box, es, CU_TENSOR_MAP_INTERLEAVE_NONE, sw,
             CU_TENSOR_MAP_L2_PROMOTION_L2_256B, CU_TENSOR_MAP_FLOAT_OOB_FILL_NONE);
}

extern "C" void kernel_launch(void* const* d_in, const int* in_sizes, int n_in, void* d_out, int out_size) {
    const bf16* x = (const bf16*)d_in[0];
    const bf16* mem0 = (const bf16*)d_in[1];
    const bf16* Wq = (const bf16*)d_in[2];
    const bf16* Wk = (const bf16*)d_in[3];
    const bf16* Wv = (const bf16*)d_in[4];
    const bf16* Wo = (const bf16*)d_in[5];
    const bf16* w1 = (const bf16*)d_in[8];
    const bf16* b1 = (const bf16*)d_in[9];
    const bf16* w2 = (const bf16*)d_in[10];
    const bf16* b2 = (const bf16*)d_in[11];
    const bf16* gw = (const bf16*)d_in[12];
    if (!g_encode) {
        void* fn = nullptr;
        cudaDriverEntryPointQueryResult st;
        cudaGetDriverEntryPoint("cuTensorMapEncodeTiled", &fn, cudaEnableDefault, &st);
        g_encode = (EncodeFn)fn;
        cudaFuncSetAttribute(worker_kernel, cudaFuncAttributeMaxDynamicSharedMemorySize, WK_SMEM);
        cudaFuncSetAttribute(chain_kernel, cudaFuncAttributeMaxDynamicSharedMemorySize, CH_SMEM);
    }
    void *hbuf, *bbuf, *obuf;
    cudaGetSymbolAddress(&hbuf, g_h);
    cudaGetSymbolAddress(&bbuf, g_b);
    cudaGetSymbolAddress(&obuf, g_o);
    const CUtensorMapSwizzle SW128 = CU_TENSOR_MAP_SWIZZLE_128B;
    cudaStream_t st = cudaStreamPerThread;

    void* xc;
    cudaGetSymbolAddress(&xc, g_xchg);
    char* xpage = (char*)(((uintptr_t)xc + (2u << 20) - 1) & ~(uintptr_t)((2u << 20) - 1));

    ChainParams cp;
    make_map(&cp.tmW[0], Wq, HD, DM, 64, 64, SW128);
    make_map(&cp.tmW[1], Wk, HD, DM, 64, 64, SW128);
    make_map(&cp.tmW[2], Wv, HD, DM, 64, 64, SW128);
    make_map(&cp.tmWo, Wo, DM, HD, 16, 128, CU_TENSOR_MAP_SWIZZLE_32B);
    make_map(&cp.tmX, x, DM, S_TOK, 64, 32, SW128);
    cp.zero = 0; cp.mem0 = mem0; cp.xmem = xpage; cp.xpart = xpage + (2u << 20);
    {
        cudaLaunchConfig_t cfg = {};
        cfg.gridDim = dim3(96); cfg.blockDim = dim3(384); cfg.dynamicSmemBytes = CH_SMEM; cfg.stream = st;
        cudaLaunchAttribute at[1];
        at[0].id = cudaLaunchAttributeClusterDimension;
        at[0].val.clusterDim.x = 3; at[0].val.clusterDim.y = 1; at[0].val.clusterDim.z = 1;
        cfg.attrs = at; cfg.numAttrs = 1;
        cudaLaunchKernelEx(&cfg, chain_kernel, cp);
    }
    WorkParams wp;
    make_map(&wp.tmA[T_FFN1], x, DM, S_TOK, 64, 128, SW128);
    make_map(&wp.tmB[T_FFN1], w1, FF, DM, 64, 64, SW128);
    make_map(&wp.tmC[T_FFN1], hbuf, FF, S_TOK, 64, 64, SW128);
    make_map(&wp.tmA[T_FFN2], hbuf, FF, S_TOK, 64, 128, SW128);
    make_map(&wp.tmB[T_FFN2], w2, DM, FF, 64, 64, SW128);
    make_map(&wp.tmC[T_FFN2], bbuf, DM, S_TOK, 64, 64, SW128);
    make_map(&wp.tmA[T_OPROJ], obuf, HD, S_TOK, 64, 128, SW128);
    make_map(&wp.tmB[T_OPROJ], Wo, DM, HD, 64, 64, SW128);
    make_map(&wp.tmC[T_OPROJ], d_out, DM, S_TOK, 64, 64, SW128);
    make_map(&wp.tmO16, obuf, HD, S_TOK, 64, 16, SW128);
    wp.bias[0] = b1; wp.bias[1] = b2; wp.x = x; wp.gw = gw;
    {
        cudaLaunchConfig_t cfg = {};
        cfg.gridDim = dim3(132); cfg.blockDim = dim3(384); cfg.dynamicSmemBytes = WK_SMEM; cfg.stream = st;
        cudaLaunchAttribute at[1];
        at[0].id = cudaLaunchAttributeProgrammaticStreamSerialization;
        at[0].val.programmaticStreamSerializationAllowed = 1;
        cfg.attrs = at; cfg.numAttrs = 1;
        cudaLaunchKernelEx(&cfg, worker_kernel, wp);
    }
}
```
